```python
import torch

def _softmax(x, axis=-1):
    return torch.softmax(x, dim=axis)
def _gelu(x):
    return torch.nn.functional.gelu(x, approximate="tanh")
def _silu(x):
    return torch.nn.functional.silu(x)
def _sigmoid(x):
    return torch.sigmoid(x)
def _layernorm(x, axis=-1, eps=1e-5):
    m = x.mean(dim=axis, keepdim=True)
    v = x.var(dim=axis, keepdim=True, unbiased=False)
    return (x - m) / torch.sqrt(v + eps)
def _scatter_add(tgt, idx, src, axis=0):
    return tgt.clone().index_add_(axis, idx, src)
def _segment_sum(src, seg, n):
    out = torch.zeros((n,) + src.shape[1:], dtype=src.dtype)
    return out.index_add_(0, seg, src)
def _pad(x, pw):
    flat = tuple(v for pair in reversed(pw) for v in pair)
    return torch.nn.functional.pad(x, flat)

kernel_name = 'sequential_preLN__sliding_block_cached__dense_activation_silu__decode'

def setup_inputs():

    _w = (lambda a: (lambda t: t.to(torch.bfloat16) if t.is_floating_point() else t)(torch.as_tensor(a)))
    def _A_setup():
        B, Sq, D = 8, 1, 640
        Hq, Hkv, Sk, Dh = 32, 32, 4096, 192
        assert Hq % Hkv == 0, (Hq, Hkv)
        return {
            "x": _w((lambda *s: torch.randn(*s, dtype=torch.bfloat16) * 0.05)(B, Sq, D)),
            "k_cache": _w((lambda *s: torch.randn(*s, dtype=torch.bfloat16) * 3.2)(B, Hkv, Sk, Dh)),
            "v_cache": _w((lambda *s: torch.randn(*s, dtype=torch.bfloat16) * 0.8)(B, Hkv, Sk, Dh)),
            "wq": _w((lambda *s: torch.randn(*s, dtype=torch.bfloat16) * 3.2)(D, Hq * Dh) * (D ** -0.5)),
            "wo": _w((lambda *s: torch.randn(*s, dtype=torch.bfloat16) * 0.8)(Hq * Dh, D) * ((Hq * Dh) ** -0.5)),
        }
    _A_in = _A_setup()

    def _B_setup():
        B, S, D, F = 8, 1, 640, 1536
        return {
            "x": _w((lambda *s: torch.randn(*s, dtype=torch.bfloat16) * 0.05)(B, S, D)),
            "w1": _w((lambda *s: torch.randn(*s, dtype=torch.bfloat16) * 3.2)(D, F) * (D ** -0.5)),
            "w2": _w((lambda *s: torch.randn(*s, dtype=torch.bfloat16) * 0.4)(F, D) * (F ** -0.5)),
        }
    _B_in = _B_setup()

    return {
        "A_x": _A_in["x"],
        "A_k_cache": _A_in["k_cache"],
        "A_v_cache": _A_in["v_cache"],
        "A_wq": _A_in["wq"],
        "A_wo": _A_in["wo"],
        "B_x": _B_in["x"],
        "B_w1": _B_in["w1"],
        "B_w2": _B_in["w2"],
    }

def reference(A_x, A_k_cache, A_v_cache, A_wq, A_wo, B_x, B_w1, B_w2):
    def _A_ref(x, k_cache, v_cache, wq, wo):
        B, Sq, D = x.shape
        Hq, Dh = 32, 192
        Hkv, Sk = k_cache.shape[1], k_cache.shape[2]
        W = min(4096, max(256, Sk // 4))
        rep = Hq // Hkv
        q = (lambda x, *d: x.permute(*d))((x @ wq).reshape(B, Sq, Hq, Dh), 0, 2, 1, 3)
        k = (lambda x, n, axis: torch.repeat_interleave(x, n, dim=axis))(k_cache[:, :, Sk - W:, :], rep, axis=1)
        v = (lambda x, n, axis: torch.repeat_interleave(x, n, dim=axis))(v_cache[:, :, Sk - W:, :], rep, axis=1)
        scores = torch.einsum("bhqd,bhkd->bhqk", q, k) * (Dh ** -0.5)
        p = _softmax(scores, axis=-1)
        o = torch.einsum("bhqk,bhkd->bhqd", p, v)
        return (lambda x, *d: x.permute(*d))(o, 0, 2, 1, 3).reshape(B, Sq, Hq * Dh) @ wo

    def _B_ref(x, w1, w2):
        h = torch.einsum("bsd,df->bsf", x, w1)
        h = _silu(h)
        out = torch.einsum("bsf,fd->bsd", h, w2)
        return out

    x = A_x
    h = x + _A_ref(_layernorm(x, axis=-1), A_k_cache, A_v_cache, A_wq, A_wo)
    h2 = h + _B_ref(_layernorm(h, axis=-1), B_w1, B_w2)
    return h2
```

```cpp
#include <cuda_runtime.h>
#include <cuda_bf16.h>
#include <cuda.h>
#include <stdint.h>

namespace {

constexpr int DM = 640, NH = 32, DH = 192, SK = 4096, WIN = 1024, FF = 1536;
constexpr int UNIT_BYTES = 24576;
constexpr int NKU = 4096, NU = 8192;
#define DRY 1
#define POLLMODE 0
#define STARTMODE 0
#define TAILN 2
#define ENDZONE 0
#define NFL 2
constexpr int NST = 8;
constexpr int NFLIGHT = NFL;
constexpr int NCW = 4;
constexpr int NGW = 10;
constexpr int NGT = NGW * 32;
constexpr int GW0 = 1 + NCW;
constexpr int NTHREADS = (GW0 + NGW) * 32;
constexpr int NCTA_Q = 96, NCTA_WO = 120, NCTA_F1 = 48, NCTA_F2 = 40;

constexpr int SM_RING = 0;
constexpr int SM_WQ   = 5 * UNIT_BYTES;
constexpr int SM_DUMMY = NST * UNIT_BYTES;
constexpr int SM_RED  = SM_WQ + 81920;
constexpr int SM_LN   = SM_RED + NGW * 2048;
constexpr int SM_BAR  = SM_LN + NGW * 64;
constexpr int SM_TOTAL = SM_BAR + 512;
static_assert(SM_TOTAL + 1024 <= 232448, "smem");
enum { B_FULL = 0, B_META = 8, B_EMPTY = 16, B_WQ = 24  , B_X = 26, B_TAG = 27, B_OKA = 28, B_OKB = 29,
       B_KA = 30, B_KB = 31, B_DONE = 32, B_WBFREE = 33, B_COUNT = 34 };
constexpr int SM_META = SM_BAR + 320;

constexpr unsigned SENT = 0xFFFFFFFFu;

struct Scratch {
    unsigned ctr[4 * 64];
    float4 h_acc[8 * 240];
    uint4 u[48 * 32];
    float4 o_acc[256 * 72];
    uint4 q[256 * 36];
    float2 stats[256 * 16];
    unsigned sc[256 * 16 * 32];
    float4 dummy[2048];
};
__device__ __align__(256) Scratch g_s;
enum { C_TICKET = 0, C_S1A = 64, C_S1B = 128 };

#define TS(i)
#define TU(u)

__device__ __forceinline__ void mbar_init(uint32_t bar, uint32_t cnt) {
    asm volatile("mbarrier.init.shared::cta.b64 [%0], %1;" ::"r"(bar), "r"(cnt) : "memory");
}
__device__ __forceinline__ void mbar_expect_tx(uint32_t bar, uint32_t bytes) {
    asm volatile("mbarrier.arrive.expect_tx.shared::cta.b64 _, [%0], %1;" ::"r"(bar), "r"(bytes) : "memory");
}
__device__ __forceinline__ void mbar_arrive(uint32_t bar) {
    asm volatile("mbarrier.arrive.shared::cta.b64 _, [%0];" ::"r"(bar) : "memory");
}
__device__ __forceinline__ void mbar_wait(uint32_t bar, uint32_t parity) {
    uint32_t ok;
#pragma unroll 1
    for (int it = 0; it < (1 << 22); ++it) {
        asm volatile("{\n.reg .pred p;\nmbarrier.try_wait.parity.shared::cta.b64 p, [%1], %2;\nselp.u32 %0, 1, 0, p;\n}"
                     : "=r"(ok) : "r"(bar), "r"(parity) : "memory");
        if (ok) return;
    }
    __trap();
}
__device__ __forceinline__ void tma2d(uint32_t dst, const CUtensorMap* tm, int c0, int c1, uint32_t bar) {
    asm volatile("cp.async.bulk.tensor.2d.shared::cluster.global.mbarrier::complete_tx::bytes [%0], [%1, {%3, %4}], [%2];"
                 ::"r"(dst), "l"(tm), "r"(bar), "r"(c0), "r"(c1) : "memory");
}
__device__ __forceinline__ void tma2d_ef(uint32_t dst, const CUtensorMap* tm, int c0, int c1, uint32_t bar) {
    uint64_t pol;
    asm volatile("createpolicy.fractional.L2::evict_first.b64 %0, 1.0;" : "=l"(pol));
    asm volatile("cp.async.bulk.tensor.2d.shared::cluster.global.mbarrier::complete_tx::bytes.L2::cache_hint [%0], [%1, {%3, %4}], [%2], %5;"
                 ::"r"(dst), "l"(tm), "r"(bar), "r"(c0), "r"(c1), "l"(pol) : "memory");
}
__device__ __forceinline__ void ldsm4(uint32_t (&r)[4], uint32_t a) {
    asm volatile("ldmatrix.sync.aligned.m8n8.x4.shared.b16 {%0,%1,%2,%3}, [%4];"
                 : "=r"(r[0]), "=r"(r[1]), "=r"(r[2]), "=r"(r[3]) : "r"(a) : "memory");
}
__device__ __forceinline__ void ldsm4t(uint32_t (&r)[4], uint32_t a) {
    asm volatile("ldmatrix.sync.aligned.m8n8.x4.trans.shared.b16 {%0,%1,%2,%3}, [%4];"
                 : "=r"(r[0]), "=r"(r[1]), "=r"(r[2]), "=r"(r[3]) : "r"(a) : "memory");
}
__device__ __forceinline__ void ldsm2(uint32_t& r0, uint32_t& r1, uint32_t a) {
    asm volatile("ldmatrix.sync.aligned.m8n8.x2.shared.b16 {%0,%1}, [%2];" : "=r"(r0), "=r"(r1) : "r"(a) : "memory");
}
__device__ __forceinline__ void mma(float (&c)[4], const uint32_t (&a)[4], uint32_t b0, uint32_t b1) {
    asm volatile("mma.sync.aligned.m16n8k16.row.col.f32.bf16.bf16.f32 {%0,%1,%2,%3}, {%4,%5,%6,%7}, {%8,%9}, {%0,%1,%2,%3};"
                 : "+f"(c[0]), "+f"(c[1]), "+f"(c[2]), "+f"(c[3])
                 : "r"(a[0]), "r"(a[1]), "r"(a[2]), "r"(a[3]), "r"(b0), "r"(b1));
}
__device__ __forceinline__ uint32_t pack2(float lo, float hi) {
    uint32_t r; asm("cvt.rn.bf16x2.f32 %0, %1, %2;" : "=r"(r) : "f"(hi), "f"(lo)); return r;
}
__device__ __forceinline__ float bf_lo(uint32_t w) { return __uint_as_float(w << 16); }
__device__ __forceinline__ float bf_hi(uint32_t w) { return __uint_as_float(w & 0xFFFF0000u); }
__device__ __forceinline__ uint32_t hadd2(uint32_t a, uint32_t b) {
    uint32_t r; asm("add.rn.bf16x2 %0, %1, %2;" : "=r"(r) : "r"(a), "r"(b)); return r;
}
__device__ __forceinline__ float rbf(float x) { return bf_lo(pack2(x, 0.f)); }

__device__ __forceinline__ unsigned ticket(unsigned* p) {
    unsigned v; asm volatile("atom.relaxed.gpu.global.inc.u32 %0, [%1], 0xFFFFFFFF;" : "=r"(v) : "l"(p) : "memory"); return v;
}
__device__ __forceinline__ void grid_barrier(unsigned* p, unsigned inc) {
    unsigned v;
    asm volatile("fence.acq_rel.gpu;\natom.relaxed.gpu.global.add.u32 %0, [%1], %2;" : "=r"(v) : "l"(p), "r"(inc) : "memory");
    const unsigned target = (v & ~8191u) + 8192u;
#pragma unroll 1
    for (int it = 0; it < (1 << 22); ++it) {
        asm volatile("ld.acquire.gpu.global.u32 %0, [%1];" : "=r"(v) : "l"(p) : "memory");
        if ((int)(v - target) >= 0) return;
    }
    __trap();
}
__device__ __forceinline__ void red4(float4* p, float a, float b, float c, float d) {
    asm volatile("red.relaxed.gpu.global.add.v4.f32 [%0], {%1,%2,%3,%4};" ::"l"(p), "f"(a), "f"(b), "f"(c), "f"(d) : "memory");
}
__device__ __forceinline__ uint4 ldcg4(const void* p) {
    uint4 v; asm volatile("ld.global.cg.v4.u32 {%0,%1,%2,%3}, [%4];" : "=r"(v.x), "=r"(v.y), "=r"(v.z), "=r"(v.w) : "l"(p) : "memory");
    return v;
}
__device__ __forceinline__ uint4 ldrlx4(const void* p) {
    uint4 v; asm volatile("ld.relaxed.gpu.global.v4.u32 {%0,%1,%2,%3}, [%4];" : "=r"(v.x), "=r"(v.y), "=r"(v.z), "=r"(v.w) : "l"(p) : "memory");
    return v;
}
__device__ __forceinline__ float4 ldrlx4f(const float4* p) {
    float4 v; asm volatile("ld.relaxed.gpu.global.v4.f32 {%0,%1,%2,%3}, [%4];" : "=f"(v.x), "=f"(v.y), "=f"(v.z), "=f"(v.w) : "l"(p) : "memory");
    return v;
}
__device__ __forceinline__ void sts4(uint32_t a, float x, float y, float z, float w) {
    asm volatile("st.shared.v4.f32 [%0], {%1,%2,%3,%4};" ::"r"(a), "f"(x), "f"(y), "f"(z), "f"(w) : "memory");
}
__device__ __forceinline__ float4 lds4(uint32_t a) {
    float4 v; asm volatile("ld.shared.v4.f32 {%0,%1,%2,%3}, [%4];" : "=f"(v.x), "=f"(v.y), "=f"(v.z), "=f"(v.w) : "r"(a) : "memory");
    return v;
}
__device__ __forceinline__ void bar_sync(int id, int n) { asm volatile("bar.sync %0, %1;" ::"r"(id), "r"(n) : "memory"); }
__device__ __forceinline__ float wsum(float v) {
#pragma unroll
    for (int o = 16; o; o >>= 1) v += __shfl_xor_sync(~0u, v, o);
    return v;
}
__device__ __forceinline__ float wmax(float v) {
#pragma unroll
    for (int o = 16; o; o >>= 1) v = fmaxf(v, __shfl_xor_sync(~0u, v, o));
    return v;
}

enum { BAR_G = 1 };

__device__ __forceinline__ void poll_frag(const float4* p, int jstride, float count, bool live, uint32_t (&bb)[8]) {
    float4 e[6];
#pragma unroll
    for (int i = 0; i < 6; ++i) e[i] = make_float4(0.f, 0.f, 0.f, live ? -1.f : count);
#pragma unroll 1
    for (int it = 0;; ++it) {
#pragma unroll
        for (int i = 0; i < 6; ++i)
            if (e[i].w != count) e[i] = ldrlx4f(p + (i >> 1) * jstride + (i & 1) * 4);
        bool ok = true;
#pragma unroll
        for (int i = 0; i < 6; ++i) ok = ok && e[i].w == count;
        if (__all_sync(~0u, ok)) break;
        if (it > (1 << 22)) __trap();
    }
    bb[0] = pack2(e[0].x, e[1].x); bb[1] = pack2(e[0].y, e[1].y); bb[2] = pack2(e[0].z, e[1].z);
    bb[3] = pack2(e[2].x, e[3].x); bb[4] = pack2(e[2].y, e[3].y); bb[5] = pack2(e[2].z, e[3].z);
    bb[6] = pack2(e[4].x, e[5].x); bb[7] = pack2(e[4].y, e[5].y);
}

__device__ __forceinline__ void layernorm_frag(uint32_t (&v)[8], uint32_t ln, int w, int g, int t) {
    float s = 0.f;
#pragma unroll
    for (int i = 0; i < 8; ++i) s += bf_lo(v[i]) + bf_hi(v[i]);
    s += __shfl_xor_sync(~0u, s, 1); s += __shfl_xor_sync(~0u, s, 2);
    const float mw = s * (1.f / 64);
    float q0 = 0.f, q1 = 0.f;
#pragma unroll
    for (int i = 0; i < 8; ++i) {
        const float d0 = bf_lo(v[i]) - mw, d1 = bf_hi(v[i]) - mw;
        q0 = fmaf(d0, d0, q0); q1 = fmaf(d1, d1, q1);
    }
    q0 += q1;
    q0 += __shfl_xor_sync(~0u, q0, 1); q0 += __shfl_xor_sync(~0u, q0, 2);
    if (t == 0) asm volatile("st.shared.v2.f32 [%0], {%1,%2};" ::"r"(ln + g * 80 + w * 8), "f"(mw), "f"(q0) : "memory");
    bar_sync(BAR_G, NGT);
    float4 z[5];
#pragma unroll
    for (int i = 0; i < 5; ++i) z[i] = lds4(ln + g * 80 + i * 16);
    const float mean = ((z[0].x + z[0].z) + (z[1].x + z[1].z) + (z[2].x + z[2].z) + (z[3].x + z[3].z) + (z[4].x + z[4].z)) * 0.1f;
    float m2 = 0.f, d2 = 0.f;
#pragma unroll
    for (int i = 0; i < 5; ++i) {
        m2 += z[i].y + z[i].w;
        const float d0 = z[i].x - mean, d1 = z[i].z - mean;
        d2 = fmaf(d0, d0, d2); d2 = fmaf(d1, d1, d2);
    }
    const float var = rbf(fmaf(64.f, d2, m2) * (1.f / DM));
    const float mb = rbf(mean);
    float sd, rs;
    asm("sqrt.approx.f32 %0, %1;" : "=f"(sd) : "f"(rbf(var + 1e-5f)));
    asm("rcp.approx.f32 %0, %1;" : "=f"(rs) : "f"(rbf(sd)));
#pragma unroll
    for (int i = 0; i < 8; ++i) {
        const uint32_t d = pack2(bf_lo(v[i]) - mb, bf_hi(v[i]) - mb);
        v[i] = pack2(bf_lo(d) * rs, bf_hi(d) * rs);
    }
}

__device__ __forceinline__ void gemv64(uint32_t wb, const uint32_t (&bb)[8], int lane) {
    const int mi = lane >> 3, r = lane & 7, g = lane >> 2, t = lane & 3;
    const uint32_t ab = wb + ((mi >> 1) * 8 + r) * 128 + (((mi & 1) ^ r) << 4);
    float acc[4][4] = {};
#pragma unroll
    for (int ks = 0; ks < 4; ++ks)
#pragma unroll
        for (int mt = 0; mt < 4; ++mt) {
            uint32_t a[4];
            ldsm4t(a, (ab ^ (mt << 5)) + ks * 2048);
            mma(acc[mt], a, bb[2 * ks], bb[2 * ks + 1]);
        }
    __syncwarp();
#pragma unroll
    for (int e = 0; e < 2; ++e) {
        const uint32_t d = wb + (2 * t + e) * 400 + g * 16;
        sts4(d, acc[0][e], acc[0][e + 2], acc[1][e], 0.f);
        sts4(d + 128, acc[1][e + 2], acc[2][e], acc[2][e + 2], 0.f);
        sts4(d + 256, acc[3][e], acc[3][e + 2], 0.f, 0.f);
    }
}

__global__ void __launch_bounds__(NTHREADS, 1)
fused_decode_kernel(const __grid_constant__ CUtensorMap tm_k, const __grid_constant__ CUtensorMap tm_v,
                    const __grid_constant__ CUtensorMap tm_wq, const __grid_constant__ CUtensorMap tm_wo,
                    const __grid_constant__ CUtensorMap tm_w1, const __grid_constant__ CUtensorMap tm_w2,
                    const __nv_bfloat16* __restrict__ x, const __nv_bfloat16* __restrict__ kc, __nv_bfloat16* __restrict__ out)
{
    extern __shared__ unsigned char smem_raw[];
    const uint32_t sb = ((uint32_t)__cvta_generic_to_shared(smem_raw) + 1023u) & ~1023u;
    const int warp = threadIdx.x >> 5, lane = threadIdx.x & 31;
    const int cta = blockIdx.x, ncta = gridDim.x;
    const uint32_t bars = sb + SM_BAR;
    const int f2 = cta - (ncta - NCTA_F2);

    const int g = lane >> 2, t = lane & 3;
    const int mi = lane >> 3, r = lane & 7;
    const int w = warp - GW0, tid = threadIdx.x - GW0 * 32;
    unsigned nxt = 0;
    if (threadIdx.x == 0) {
        TS(0);
        mbar_init(bars + B_WQ * 8, 1); mbar_init(bars + B_WQ * 8 + 8, 1); mbar_init(bars + B_FULL * 8, 1);
        asm volatile("fence.mbarrier_init.release.cluster;" ::: "memory");
        if (cta < NCTA_Q) {
            mbar_expect_tx(bars + B_WQ * 8, 40960);
            tma2d_ef(sb + SM_WQ, &tm_wq, cta * 64, 0, bars + B_WQ * 8);
            tma2d_ef(sb + SM_WQ + 20480, &tm_wq, cta * 64, 160, bars + B_WQ * 8);
            mbar_expect_tx(bars + B_WQ * 8 + 8, 40960);
            tma2d_ef(sb + SM_WQ + 40960, &tm_wq, cta * 64, 320, bars + B_WQ * 8 + 8);
            tma2d_ef(sb + SM_WQ + 61440, &tm_wq, cta * 64, 480, bars + B_WQ * 8 + 8);
        }
        mbar_expect_tx(bars + B_FULL * 8, UNIT_BYTES);
        tma2d_ef(sb + SM_RING, &tm_k, 0, (int)(((cta >> 4) * SK + (SK - WIN) + (cta & 15) * 64) * 3), bars + B_FULL * 8);
    }
    if (threadIdx.x == 96) {
        mbar_init(bars + B_X * 8, 1);
        asm volatile("fence.mbarrier_init.release.cluster;" ::: "memory");
        mbar_expect_tx(bars + B_X * 8, 8 * DM * 2);
        asm volatile("cp.async.bulk.shared::cluster.global.mbarrier::complete_tx::bytes [%0], [%1], %2, [%3];"
                     ::"r"(sb + SM_RED), "l"(x), "r"(8 * DM * 2), "r"(bars + B_X * 8) : "memory");
    }
    if (threadIdx.x == 128) {
        nxt = ticket(&g_s.ctr[C_TICKET]);
    }
    if (threadIdx.x >= 32 && threadIdx.x < 32 + B_COUNT) {
        const int i = threadIdx.x - 32;
        if (i != B_FULL && (i < B_WQ || i > B_X)) mbar_init(bars + i * 8, (i >= B_KA && i <= B_DONE) ? NCW : 1);
        asm volatile("fence.mbarrier_init.release.cluster;" ::: "memory");
    }
    __syncthreads();
    if (threadIdx.x == 128) {
        asm volatile("st.shared.u32 [%0], %1;" ::"r"(sb + SM_META + 36), "r"(nxt) : "memory");
        mbar_arrive(bars + B_TAG * 8);
    }

    if (warp == 0) {
        if (lane == 0) {
            asm volatile("st.shared.u32 [%0], %1;" ::"r"(sb + SM_META), "r"(cta) : "memory");
            mbar_arrive(bars + B_META * 8);
            mbar_wait(bars + B_TAG * 8, 0);
            asm volatile("ld.shared.u32 %0, [%1];" : "=r"(nxt) : "r"(sb + SM_META + 36) : "memory");
            int k = -1;
#pragma unroll 1
            for (int i = 1; k < 4; ++i) {
                const int s = i & (NST - 1);
                const CUtensorMap* tm;
                int c0, c1, nb, rows, bytes;
                unsigned u = NU;
                if (k < 0) {
                    u = (nxt & (NU - 1)) + ncta;
                    if (u >= NU) {
                        TS(2);
                        asm volatile("st.shared.u32 [%0], %1;" ::"r"(sb + SM_META + 32), "r"(i) : "memory");
#pragma unroll 1
                        for (int j = i; j < i + NCW; ++j) {
                            mbar_wait(bars + (B_EMPTY + (j & (NST - 1))) * 8, ((j >> 3) - 1) & 1);
                            asm volatile("st.shared.u32 [%0], %1;" ::"r"(sb + SM_META + (j & (NST - 1)) * 4), "r"(NU) : "memory");
                            mbar_arrive(bars + (B_META + (j & (NST - 1))) * 8);
                        }
                    }
                }
                if (u < NU) {
                    const unsigned uu = u & (NKU - 1);
                    tm = u < NKU ? &tm_k : &tm_v;
                    c0 = 0; c1 = (int)(((uu >> 4) * SK + (SK - WIN) + (uu & 15) * 64) * 3);
                    nb = 1; rows = 0; bytes = UNIT_BYTES;
                } else {
                    ++k;
                    const bool is_wo = k < 3, is_w1 = cta < NCTA_F1;
                    tm = is_wo ? &tm_wo : is_w1 ? &tm_w1 : &tm_w2;
                    c0 = is_wo ? (cta % 10) * 64 : is_w1 ? cta * 32 : f2 * 16;
                    c1 = is_wo ? (cta / 10) * 512 + k * 192 : (k - 3) * (is_w1 ? 320 : 768);
                    nb = is_wo ? (cta < NCTA_WO ? (k < 2 ? 3 : 2) : 0) : is_w1 ? 2 : f2 >= 0 ? 3 : 0;
                    rows = is_wo ? 64 : is_w1 ? 160 : 256;
                    bytes = (!is_wo && is_w1) ? 10240 : 8192;
                }
                const int nf = (k >= 0 || u >= NU - ENDZONE) ? TAILN : NFLIGHT;
                if (i >= nf) mbar_wait(bars + (B_FULL + ((i - nf) & (NST - 1))) * 8, ((i - nf) >> 3) & 1);
                if (k == 3 && f2 >= 0) mbar_wait(bars + (B_FULL + ((i - 1) & (NST - 1))) * 8, ((i - 1) >> 3) & 1);
                if (i >= NST) mbar_wait(bars + (B_EMPTY + s) * 8, ((i >> 3) - 1) & 1);
                else if (i == 5) mbar_wait(bars + B_WBFREE * 8, 0);
                if (k < 0) {
                    asm volatile("st.shared.u32 [%0], %1;" ::"r"(sb + SM_META + s * 4), "r"(u) : "memory");
                    mbar_arrive(bars + (B_META + s) * 8);
                }
                mbar_expect_tx(bars + (B_FULL + s) * 8, nb * bytes);
#pragma unroll 1
                for (int j = 0; j < nb; ++j)
                    tma2d_ef(sb + SM_RING + s * UNIT_BYTES + j * bytes, tm, c0, c1 + j * rows, bars + (B_FULL + s) * 8);
                if (k < 0) nxt = ticket(&g_s.ctr[C_TICKET]);
                if (i == 16) {
                    asm volatile("prefetch.tensormap [%0];" ::"l"(&tm_v) : "memory");
                    asm volatile("prefetch.tensormap [%0];" ::"l"(&tm_wo) : "memory");
                    asm volatile("prefetch.tensormap [%0];" ::"l"(&tm_w1) : "memory");
                    asm volatile("prefetch.tensormap [%0];" ::"l"(&tm_w2) : "memory");
                }
            }
            TS(3);
        }
        return;
    }

    if (warp < GW0) {
        uint32_t ka[3], va[3];
        {
            const int key = (mi & 1) ? 8 + ((r + 4) & 7) : r, hi = mi >> 1;
            const int gg = (r >> 1) + 4 * (mi >> 1);
            const int vkey = (r & 1) ? 8 + ((gg + 4) & 7) : gg, vhi = mi & 1;
#pragma unroll
            for (int th = 0; th < 3; ++th) {
                ka[th] = (key * 3 + th) * 128 + ((hi ^ ((key * 3 + th) & 7)) << 4);
                va[th] = (vkey * 3 + th) * 128 + ((vhi ^ ((vkey * 3 + th) & 7)) << 4);
            }
        }
        mbar_wait(bars + B_TAG * 8, 0);
        unsigned tag;
        asm volatile("ld.shared.u32 %0, [%1];" : "=r"(tag) : "r"(sb + SM_META + 36) : "memory");
        tag |= NU - 1;
        mbar_wait(bars + B_WBFREE * 8, 0);
        int phase = 0;
#pragma unroll 1
        for (int i = warp - 1;; i += NCW) {
            const int s = i & (NST - 1);
            const uint32_t par = (i >> 3) & 1;
            const uint32_t stage = sb + SM_RING + s * UNIT_BYTES;
            mbar_wait(bars + (B_META + s) * 8, par);
            unsigned u;
            asm volatile("ld.shared.u32 %0, [%1];" : "=r"(u) : "r"(sb + SM_META + s * 4) : "memory");
            const int ph = u >> 11;
            if (ph != phase) {
                __syncwarp();
                if (lane == 0) {
                    if (phase < 1) mbar_arrive(bars + B_KA * 8);
                    if (phase < 2 && ph >= 2) mbar_arrive(bars + B_KB * 8);
                    if (ph == 4) mbar_arrive(bars + B_DONE * 8);
                }
                if (ph == 4) break;
                if (ph >= 2) mbar_wait(bars + (ph == 2 ? B_OKA : B_OKB) * 8, 0);
                phase = ph;
            }
            const unsigned item = (u & (NKU - 1)) >> 4, chunk = u & 15;
            if (u < NKU) {
                uint32_t qf[24];
                const uint4* qp = g_s.q + item * 36 + t * 9;
#pragma unroll 1
                for (int it = 0;; ++it) {
                    bool ok = true;
#pragma unroll
                    for (int j = 0; j < 9; ++j) {
                        const uint4 v = ldrlx4(qp + j);
                        const int c = (j / 3) * 8 + (j % 3) * 3;
                        qf[c] = v.x; qf[c + 1] = v.y;
                        if (j % 3 < 2) qf[c + 2] = v.z;
                        ok = ok && v.w == tag;
                    }
                    if (__all_sync(~0u, ok)) break;
                    if (it > (1 << 22)) __trap();
                    __nanosleep(100);
                }
                mbar_wait(bars + (B_FULL + s) * 8, par);
                TU(u);
                float acc[4][4] = {};
#pragma unroll
                for (int ks = 0; ks < 12; ++ks) {
                    const uint32_t a0 = stage + (ka[ks >> 2] ^ ((ks & 3) << 5));
#pragma unroll
                    for (int kt = 0; kt < 4; ++kt) {
                        uint32_t a[4];
                        ldsm4(a, a0 + kt * 6144);
                        mma(acc[kt], a, qf[2 * ks], qf[2 * ks + 1]);
                    }
                }
                float s0 = t == 0 ? acc[0][0] : t == 1 ? acc[1][0] : t == 2 ? acc[2][0] : acc[3][0];
                float s1 = t == 0 ? acc[0][2] : t == 1 ? acc[1][2] : t == 2 ? acc[2][2] : acc[3][2];
                const float scale = 0.07216878364870322f;
                uint32_t w = pack2(s0, s1);
                __syncwarp();
                if (lane == 0) mbar_arrive(bars + (B_EMPTY + s) * 8);
                w = pack2(bf_lo(w) * scale, bf_hi(w) * scale);
                s0 = bf_lo(w); s1 = bf_hi(w);
                const float m = wmax(fmaxf(s0, s1));
                const float l = wsum(__expf(s0 - m) + __expf(s1 - m));
                g_s.sc[(item * 16 + chunk) * 32 + lane] = w;
                if (lane == 0) g_s.stats[item * 16 + chunk] = make_float2(m, l);
            } else {
                uint32_t w; float2 st;
                asm volatile("ld.global.cg.u32 %0, [%1];" : "=r"(w) : "l"(g_s.sc + (item * 16 + chunk) * 32 + lane) : "memory");
                asm volatile("ld.global.cg.v2.f32 {%0,%1}, [%2];" : "=f"(st.x), "=f"(st.y) : "l"(g_s.stats + item * 16 + (lane & 15)) : "memory");
                const float m = wmax(st.x);
                const float rl = __fdividef(2.f, wsum(st.y * __expf(st.x - m)));
                const uint32_t p = pack2(__expf(bf_lo(w) - m) * rl, __expf(bf_hi(w) - m) * rl);
                uint32_t pb[8];
#pragma unroll
                for (int kt = 0; kt < 4; ++kt) {
                    pb[2 * kt] = __shfl_sync(~0u, p, 4 * t + kt);
                    pb[2 * kt + 1] = __shfl_sync(~0u, p, 16 + 4 * t + kt);
                }
                mbar_wait(bars + (B_FULL + s) * 8, par);
                TU(u);
                float acc[12][4] = {};
#pragma unroll
                for (int kt = 0; kt < 4; ++kt) {
#pragma unroll
                    for (int dt = 0; dt < 12; ++dt) {
                        uint32_t a[4];
                        ldsm4t(a, stage + (va[dt >> 2] ^ ((dt & 3) << 5)) + kt * 6144);
                        mma(acc[dt], a, pb[2 * kt], pb[2 * kt + 1]);
                    }
                }
                float o[8];
#pragma unroll
                for (int j = 0; j < 4; ++j) {
                    o[2 * j] = t == 0 ? acc[j][0] : t == 1 ? acc[4 + j][0] : acc[8 + j][0];
                    o[2 * j + 1] = t == 0 ? acc[j][2] : t == 1 ? acc[4 + j][2] : acc[8 + j][2];
                }
                if (t < 3) {
                    float4* op = g_s.o_acc + item * 72 + t * 8 + (g & 1) * 4 + (g >> 1);
                    red4(op, o[0], o[1], o[2], 1.f);
                    red4(op + 24, o[3], o[4], o[5], 1.f);
                    red4(op + 48, o[6], o[7], 0.f, 1.f);
                }
                __syncwarp();
                if (lane == 0) mbar_arrive(bars + (B_EMPTY + s) * 8);
            }
        }
        return;
    }

    {
        constexpr int NH4 = 8 * 240, NU4 = 48 * 32, NALL = NH4 + NU4 + 256 * 72;
#pragma unroll 1
        for (int i = cta * NGT + tid; i < NALL; i += ncta * NGT) {
            const unsigned f = (i >= NH4 && i < NH4 + NU4) ? SENT : 0u;
            reinterpret_cast<uint4*>(g_s.h_acc)[i] = make_uint4(f, f, f, f);
        }
    }
    const uint32_t red = sb + SM_RED, ln = sb + SM_LN;
    uint32_t xr[8], xres;
    mbar_wait(bars + B_X * 8, 0);
#pragma unroll
    for (int c = 0; c < 8; ++c)
        asm volatile("ld.shared.u32 %0, [%1];" : "=r"(xr[c]) : "r"(red + (g * DM + w * 64 + c * 8 + 2 * t) * 2) : "memory");
    asm volatile("ld.shared.u16 %0, [%1];" : "=r"(xres) : "r"(red + ((2 * t + (w & 1)) * DM + max(f2, 0) * 16 + ((w >> 1) & 1) * 8 + g) * 2) : "memory");
    const int rb = tid / 24, rj = tid % 24;
    if (cta < NCTA_Q) {
        uint32_t bb[8];
#pragma unroll
        for (int c = 0; c < 8; ++c) bb[c] = xr[c];
        layernorm_frag(bb, ln, w, g, t);
        mbar_wait(bars + (B_WQ + (w >= 5)) * 8, 0);
        if (tid == 224) TS(8);
        gemv64(sb + SM_WQ + w * 8192, bb, lane);
        bar_sync(BAR_G, NGT);
        if (tid < 192) {
            float s0 = 0.f, s1 = 0.f, s2 = 0.f;
#pragma unroll
            for (int k = 0; k < NGW; ++k) {
                const float4 v = lds4(sb + SM_WQ + k * 8192 + rb * 400 + rj * 16);
                s0 += v.x; s1 += v.y; s2 += v.z;
            }
            const float n0 = __shfl_xor_sync(~0u, s0, 1), n1 = __shfl_xor_sync(~0u, s1, 1), n2 = __shfl_xor_sync(~0u, s2, 1);
            if (!(rj & 1)) {
                mbar_wait(bars + B_TAG * 8, 0);
                unsigned tag;
                asm volatile("ld.shared.u32 %0, [%1];" : "=r"(tag) : "r"(sb + SM_META + 36) : "memory");
                asm volatile("st.relaxed.gpu.global.v4.u32 [%0], {%1,%2,%3,%4};"
                             ::"l"(g_s.q + (rb * NH + cta / 3) * 36 + ((rj & 7) >> 1) * 9 + (cta % 3) * 3 + (rj >> 3)),
                               "r"(pack2(s0, n0)), "r"(pack2(s1, n1)), "r"(pack2(s2, n2)), "r"(tag | (NU - 1)) : "memory");
            }
        }
        asm volatile("fence.proxy.async.shared::cta;" ::: "memory");
    }
    bar_sync(BAR_G, NGT);
#pragma unroll 1
    for (int pass = DRY ? 0 : 1; pass < 2; ++pass) {
        const bool live = pass != 0;
        if (tid == 0) {
            if (!live || !DRY) {
                const unsigned inc = cta == 0 ? 8193u - ncta : 1u;
                mbar_arrive(bars + B_WBFREE * 8);
                TS(9);
                mbar_wait(bars + B_KA * 8, 0);
                grid_barrier(&g_s.ctr[C_S1A], inc);
                mbar_arrive(bars + B_OKA * 8);
                mbar_wait(bars + B_KB * 8, 0);
                grid_barrier(&g_s.ctr[C_S1B], inc);
                mbar_arrive(bars + B_OKB * 8);
            }
            if (live) {
                mbar_wait(bars + B_DONE * 8, 0);
                TS(4);
            }
        }
        __syncwarp();
        bar_sync(BAR_G, NGT);
        unsigned tail;
        asm volatile("ld.shared.u32 %0, [%1];" : "=r"(tail) : "r"(sb + SM_META + 32) : "memory");
        if (cta < NCTA_WO) {
            if (w < 8) {
                const int third = (cta / 10) * 8 + w;
                uint32_t bb[8];
                poll_frag(g_s.o_acc + (g * NH + third / 3) * 72 + (third % 3) * 8 + t, 24, 16.f, live, bb);
                if (tid == 224) TS(12);
                const unsigned iw = tail + w / 3;
                if (live) mbar_wait(bars + (B_FULL + (iw & 7)) * 8, (iw >> 3) & 1);
                if (tid == 224) TS(13);
                gemv64(live ? sb + SM_RING + (iw & 7) * UNIT_BYTES + (w % 3) * 8192 : sb + SM_DUMMY, bb, lane);
            }
            bar_sync(BAR_G, NGT);
            if (tid < 192) {
                float s0 = 0.f, s1 = 0.f, s2 = 0.f;
#pragma unroll
                for (int k = 0; k < 8; ++k) {
                    const float4 v = lds4(sb + SM_RING + ((tail + k / 3) & 7) * UNIT_BYTES + (k % 3) * 8192 + rb * 400 + rj * 16);
                    s0 += v.x; s1 += v.y; s2 += v.z;
                }
                red4((live ? g_s.h_acc : g_s.dummy) + rb * 240 + (cta % 10) * 24 + (rj & 24) + (rj & 1) * 4 + ((rj & 7) >> 1), s0, s1, s2, 1.f);
            }
            if (tid == 0) TS(14);
        }
        if (cta < NCTA_F1) {
            constexpr uint32_t ONES = 0x3F803F80u;
            uint32_t a[8][4];
            const unsigned i1 = tail + 3 + (w >= 5);
            const uint32_t ab = sb + SM_RING + (i1 & 7) * UNIT_BYTES + ((w % 5) * 64 + (mi >> 1) * 8 + r) * 64 + (((mi & 1) ^ (r >> 1)) << 4);
            unsigned* up = reinterpret_cast<unsigned*>((live ? g_s.u : reinterpret_cast<uint4*>(g_s.dummy)) + cta * 32 + 8 * t + (w & 1) * 4 + (g & 3)) + (w & 2) + (g >> 2);
            if (live) mbar_wait(bars + (B_FULL + (i1 & 7)) * 8, (i1 >> 3) & 1);
            if (tid == 224) TS(15);
#pragma unroll
            for (int ks = 0; ks < 4; ++ks) { ldsm4t(a[2 * ks], ab + ks * 1024); ldsm4t(a[2 * ks + 1], (ab ^ 32) + ks * 1024); }
            float cs[2][4] = {};
#pragma unroll
            for (int ks = 0; ks < 4; ++ks) { mma(cs[0], a[2 * ks], ONES, ONES); mma(cs[1], a[2 * ks + 1], ONES, ONES); }
            uint32_t bb[8];
            poll_frag(g_s.h_acc + g * 240 + w * 24 + t, 8, 12.f, live, bb);
            if (tid == 0) TS(16);
            float acc[3][4] = {};
#pragma unroll
            for (int ks = 0; ks < 4; ++ks) {
                const uint32_t h0 = hadd2(xr[2 * ks], bb[2 * ks]), h1 = hadd2(xr[2 * ks + 1], bb[2 * ks + 1]);
                const uint32_t ha[4] = {h0, ONES, h1, ONES};
                mma(acc[0], a[2 * ks], h0, h1);
                mma(acc[1], a[2 * ks + 1], h0, h1);
                mma(acc[2], ha, h0, h1);
            }
#pragma unroll
            for (int j = 0; j < 4; ++j)
                sts4(red + w * 2048 + j * 512 + lane * 16, acc[j >> 1][j & 1], acc[j >> 1][(j & 1) + 2], cs[j >> 1][0], cs[j >> 1][2]);
            if ((g >> 1) == t)
                asm volatile("st.shared.v2.f32 [%0], {%1,%2};" ::"r"(ln + g * 80 + w * 8), "f"((g & 1) ? acc[2][3] : acc[2][2]),
                             "f"((g & 1) ? acc[2][1] : acc[2][0]) : "memory");
            bar_sync(BAR_G, NGT);
            if (w < 4) {
                float4 v[NGW], z[5];
#pragma unroll
                for (int i = 0; i < 5; ++i) z[i] = lds4(ln + (2 * t + (w & 1)) * 80 + i * 16);
#pragma unroll
                for (int k = 0; k < NGW; ++k) v[k] = lds4(red + k * 2048 + w * 512 + lane * 16);
                const float mean = (((z[0].x + z[0].z) + (z[1].x + z[1].z)) + ((z[2].x + z[2].z) + (z[3].x + z[3].z)) + (z[4].x + z[4].z)) * (1.f / DM);
                const float msq = (((z[0].y + z[0].w) + (z[1].y + z[1].w)) + ((z[2].y + z[2].w) + (z[3].y + z[3].w)) + (z[4].y + z[4].w)) * (1.f / DM);
                const float var = rbf(fmaxf(fmaf(-mean, mean, msq), 0.f));
                const float mb = rbf(mean);
                float sd, rs;
                asm("sqrt.approx.ftz.f32 %0, %1;" : "=f"(sd) : "f"(rbf(var + 1e-5f)));
                asm("rcp.approx.ftz.f32 %0, %1;" : "=f"(rs) : "f"(rbf(sd)));
#pragma unroll
                for (int k = 0; k < 5; ++k) { v[k].x += v[k + 5].x; v[k].y += v[k + 5].y; v[k].z += v[k + 5].z; v[k].w += v[k + 5].w; }
                const float a0 = ((v[0].x + v[1].x) + (v[2].x + v[3].x)) + v[4].x, a1 = ((v[0].y + v[1].y) + (v[2].y + v[3].y)) + v[4].y;
                const float c0 = ((v[0].z + v[1].z) + (v[2].z + v[3].z)) + v[4].z, c1 = ((v[0].w + v[1].w) + (v[2].w + v[3].w)) + v[4].w;
                const uint32_t zz = pack2(fmaf(-mb, c0, a0) * rs, fmaf(-mb, c1, a1) * rs);
                const float z0 = bf_lo(zz), z1 = bf_hi(zz);
                float e0, e1;
                asm("ex2.approx.ftz.f32 %0, %1;" : "=f"(e0) : "f"(z0 * -1.4426950408889634f));
                asm("ex2.approx.ftz.f32 %0, %1;" : "=f"(e1) : "f"(z1 * -1.4426950408889634f));
                asm("rcp.approx.ftz.f32 %0, %1;" : "=f"(e0) : "f"(1.f + e0));
                asm("rcp.approx.ftz.f32 %0, %1;" : "=f"(e1) : "f"(1.f + e1));
                asm volatile("st.relaxed.gpu.global.u32 [%0], %1;" ::"l"(up), "r"(pack2(z0 * e0, z1 * e1)) : "memory");
                if (tid == 0) TS(17);
            }
        } else if (f2 >= 0 && w < 8) {
            uint32_t a[12][4];
            const unsigned i2 = tail + 3 + (w >> 2);
            if (live) mbar_wait(bars + (B_FULL + (i2 & 7)) * 8, (i2 >> 3) & 1);
            if (tid == 224) TS(20);
            {
                const int row = (mi >> 1) * 4 + (r >> 1) + (r & 1) * 8;
                const uint32_t ab = sb + SM_RING + (i2 & 7) * UNIT_BYTES + ((w & 3) * 192 + row) * 32 + (((mi & 1) ^ ((row >> 2) & 1)) << 4);
#pragma unroll
                for (int ks = 0; ks < 12; ++ks) ldsm4t(a[ks], ab + ks * 512);
            }
            float hres = 0.f;
            __nv_bfloat16* op = (live ? out : reinterpret_cast<__nv_bfloat16*>(g_s.dummy + 1024)) + (2 * t + (w & 1)) * DM + f2 * 16 + ((w >> 1) & 1) * 8 + g;
            if (w < 4) {
                const int ch = (f2 & 3) * 2 + (w >> 1);
                float4 v = make_float4(0.f, 0.f, 0.f, live ? -1.f : 12.f);
#pragma unroll 1
                for (int it = 0;; ++it) {
                    if (v.w != 12.f) v = ldrlx4f(g_s.h_acc + (2 * t + (w & 1)) * 240 + (f2 >> 2) * 24 + (ch / 3) * 8 + (g & 1) * 4 + (g >> 1));
                    if (__all_sync(~0u, v.w == 12.f)) break;
                    if (it > (1 << 22)) __trap();
                }
                hres = rbf(bf_lo(xres) + rbf(ch % 3 == 0 ? v.x : ch % 3 == 1 ? v.y : v.z));
            }
            bar_sync(2, 256);
            uint4 uu[6];
            unsigned mx[6];
            const uint4* up = g_s.u + w * 6 * 32 + lane;
#pragma unroll
            for (int i = 0; i < 6; ++i) { uu[i] = make_uint4(0u, 0u, 0u, 0u); mx[i] = live ? SENT : 0u; }
#pragma unroll 1
            for (int it = 0;; ++it) {
#pragma unroll
                for (int i = 0; i < 6; ++i)
                    if (mx[i] == SENT) uu[i] = ldrlx4(up + i * 32);
#pragma unroll
                for (int i = 0; i < 6; ++i) mx[i] = max(max(uu[i].x, uu[i].y), max(uu[i].z, uu[i].w));
                if (__all_sync(~0u, max(max(max(mx[0], mx[1]), max(mx[2], mx[3])), max(mx[4], mx[5])) != SENT)) break;
                if (it > (1 << 22)) __trap();
            }
            if (tid == 0) TS(18);
            float acc[4][4] = {};
#pragma unroll
            for (int i = 0; i < 6; ++i) {
                mma(acc[(2 * i) & 3], a[2 * i], uu[i].x, uu[i].y);
                mma(acc[(2 * i + 1) & 3], a[2 * i + 1], uu[i].z, uu[i].w);
            }
#pragma unroll
            for (int c = 0; c < 4; ++c)
                asm volatile("st.shared.f32 [%0], %1;" ::"r"(red + w * 512 + c * 128 + lane * 4),
                             "f"((acc[0][c] + acc[1][c]) + (acc[2][c] + acc[3][c])) : "memory");
            bar_sync(2, 256);
            if (w < 4) {
                float v[8];
#pragma unroll
                for (int k = 0; k < 8; ++k)
                    asm volatile("ld.shared.f32 %0, [%1];" : "=f"(v[k]) : "r"(red + k * 512 + w * 128 + lane * 4) : "memory");
                *op = __float2bfloat16(hres + rbf(((v[0] + v[1]) + (v[2] + v[3])) + ((v[4] + v[5]) + (v[6] + v[7]))));
                if (tid == 0) TS(19);
            }
        }
    }
}

typedef CUresult (*EncodeFn)(CUtensorMap*, CUtensorMapDataType, cuuint32_t, void*, const cuuint64_t*, const cuuint64_t*,
                             const cuuint32_t*, const cuuint32_t*, CUtensorMapInterleave, CUtensorMapSwizzle,
                             CUtensorMapL2promotion, CUtensorMapFloatOOBfill);

void make_map(EncodeFn enc, CUtensorMap* m, void* base, uint64_t cols, uint64_t rows, uint32_t bc, uint32_t br,
              CUtensorMapSwizzle sw, CUtensorMapL2promotion promo) {
    cuuint64_t dims[2] = {cols, rows};
    cuuint64_t strides[1] = {cols * 2};
    cuuint32_t box[2] = {bc, br};
    cuuint32_t es[2] = {1, 1};
    enc(m, CU_TENSOR_MAP_DATA_TYPE_BFLOAT16, 2, base, dims, strides, box, es, CU_TENSOR_MAP_INTERLEAVE_NONE, sw, promo,
        CU_TENSOR_MAP_FLOAT_OOB_FILL_NONE);
}

}

extern "C" void kernel_launch(void* const* d_in, const int* in_sizes, int n_in, void* d_out, int out_size) {
    (void)in_sizes; (void)n_in; (void)out_size;
    void* fn = nullptr;
    cudaDriverEntryPointQueryResult qr;
    cudaGetDriverEntryPoint("cuTensorMapEncodeTiled", &fn, cudaEnableDefault, &qr);
    EncodeFn enc = (EncodeFn)fn;
    CUtensorMap tk, tv, tq, to, t1, t2;
    const uint64_t kv_lines = 8ull * NH * SK * 3;
    make_map(enc, &tk, d_in[1], 64, kv_lines, 64, 192, CU_TENSOR_MAP_SWIZZLE_128B, CU_TENSOR_MAP_L2_PROMOTION_L2_128B);
    make_map(enc, &tv, d_in[2], 64, kv_lines, 64, 192, CU_TENSOR_MAP_SWIZZLE_128B, CU_TENSOR_MAP_L2_PROMOTION_L2_128B);
    make_map(enc, &tq, d_in[3], NH * DH, DM, 64, 160, CU_TENSOR_MAP_SWIZZLE_128B, CU_TENSOR_MAP_L2_PROMOTION_L2_128B);
    make_map(enc, &to, d_in[4], DM, NH * DH, 64, 64, CU_TENSOR_MAP_SWIZZLE_128B, CU_TENSOR_MAP_L2_PROMOTION_L2_128B);
    make_map(enc, &t1, d_in[6], FF, DM, 32, 160, CU_TENSOR_MAP_SWIZZLE_64B, CU_TENSOR_MAP_L2_PROMOTION_L2_128B);
    make_map(enc, &t2, d_in[7], DM, FF, 16, 256, CU_TENSOR_MAP_SWIZZLE_32B, CU_TENSOR_MAP_L2_PROMOTION_L2_128B);
    int dev = 0, sms = 0;
    cudaGetDevice(&dev);
    cudaDeviceGetAttribute(&sms, cudaDevAttrMultiProcessorCount, dev);
    cudaFuncSetAttribute(fused_decode_kernel, cudaFuncAttributeMaxDynamicSharedMemorySize, SM_TOTAL + 1024);
    fused_decode_kernel<<<sms, NTHREADS, SM_TOTAL + 1024, cudaStreamPerThread>>>(
        tk, tv, tq, to, t1, t2, (const __nv_bfloat16*)d_in[0], (const __nv_bfloat16*)d_in[1], (__nv_bfloat16*)d_out);
}
```

```cpp
#include <cuda_runtime.h>
#include <cuda_bf16.h>
#include <cuda.h>
#include <stdint.h>

namespace {

constexpr int DM = 640, NH = 32, DH = 192, SK = 4096, WIN = 1024, FF = 1536;
constexpr int UNIT_BYTES = 24576;
constexpr int NKU = 4096, NU = 8192;
constexpr int NTOT = NU + 320;
constexpr unsigned END = 0x7FFFFFFFu;
constexpr int NST = 8;
constexpr int NFLIGHT = 2;
constexpr int ENDZ = 132;
constexpr int PD = 400;
constexpr int W1D = 1600, W2D = 300;
constexpr int NCW = 4;
constexpr int NGW = 10;
constexpr int NGT = NGW * 32;
constexpr int GW0 = 1 + NCW;
constexpr int NTHREADS = (GW0 + NGW) * 32;
constexpr int NCTA = 132;
constexpr int NCTA_Q = 96, NCTA_F1 = 48, NCTA_F2 = 40;

constexpr int SM_RING = 0;
constexpr int SM_WQ   = 5 * UNIT_BYTES;
constexpr int SM_RED  = SM_WQ + 81920;
constexpr int SM_LN   = SM_RED + NGW * 2048;
constexpr int SM_BAR  = SM_LN + NGW * 64;
constexpr int SM_TOTAL = SM_BAR + 512;
static_assert(SM_TOTAL + 1024 <= 232448, "smem");
enum { B_FULL = 0, B_META = 8, B_EMPTY = 16, B_WQ = 24  , B_X = 26, B_TAG = 27, B_OKA = 28, B_OKB = 29,
       B_KA = 30, B_KB = 31, B_DONE = 32, B_WBFREE = 33, B_TAIL = 34, B_COUNT = 35 };
constexpr int SM_META = SM_BAR + 320;

constexpr unsigned SENT = 0xFFFFFFFFu;

struct Scratch {
    unsigned ctr[4 * 64];
    float4 h_acc[8 * 240];
    uint4 u[48 * 32];
    float4 o_acc[256 * 72];
    uint4 q[256 * 36];
    float2 stats[256 * 16];
    unsigned sc[256 * 16 * 32];
};
__device__ __align__(256) Scratch g_s;
enum { C_TICKET = 0, C_S1A = 64, C_S1B = 128 };

__device__ __forceinline__ void mbar_init(uint32_t bar, uint32_t cnt) {
    asm volatile("mbarrier.init.shared::cta.b64 [%0], %1;" ::"r"(bar), "r"(cnt) : "memory");
}
__device__ __forceinline__ void mbar_expect_tx(uint32_t bar, uint32_t bytes) {
    asm volatile("mbarrier.arrive.expect_tx.shared::cta.b64 _, [%0], %1;" ::"r"(bar), "r"(bytes) : "memory");
}
__device__ __forceinline__ void mbar_arrive(uint32_t bar) {
    asm volatile("mbarrier.arrive.shared::cta.b64 _, [%0];" ::"r"(bar) : "memory");
}
__device__ __forceinline__ void mbar_wait(uint32_t bar, uint32_t parity) {
    uint32_t ok;
#pragma unroll 1
    for (int it = 0; it < (1 << 22); ++it) {
        asm volatile("{\n.reg .pred p;\nmbarrier.try_wait.parity.shared::cta.b64 p, [%1], %2;\nselp.u32 %0, 1, 0, p;\n}"
                     : "=r"(ok) : "r"(bar), "r"(parity) : "memory");
        if (ok) return;
    }
    __trap();
}
__device__ __forceinline__ void tma2d_ef(uint32_t dst, const CUtensorMap* tm, int c0, int c1, uint32_t bar) {
    uint64_t pol;
    asm volatile("createpolicy.fractional.L2::evict_first.b64 %0, 1.0;" : "=l"(pol));
    asm volatile("cp.async.bulk.tensor.2d.shared::cluster.global.mbarrier::complete_tx::bytes.L2::cache_hint [%0], [%1, {%3, %4}], [%2], %5;"
                 ::"r"(dst), "l"(tm), "r"(bar), "r"(c0), "r"(c1), "l"(pol) : "memory");
}
__device__ __forceinline__ void tma3d(uint32_t dst, const CUtensorMap* tm, int c0, int c2, uint32_t bar) {
    asm volatile("cp.async.bulk.tensor.3d.shared::cluster.global.mbarrier::complete_tx::bytes [%0], [%1, {%3, %5, %4}], [%2];"
                 ::"r"(dst), "l"(tm), "r"(bar), "r"(c0), "r"(c2), "r"(0) : "memory");
}
__device__ __forceinline__ void ldsm4(uint32_t (&r)[4], uint32_t a) {
    asm volatile("ldmatrix.sync.aligned.m8n8.x4.shared.b16 {%0,%1,%2,%3}, [%4];"
                 : "=r"(r[0]), "=r"(r[1]), "=r"(r[2]), "=r"(r[3]) : "r"(a) : "memory");
}
__device__ __forceinline__ void ldsm4t(uint32_t (&r)[4], uint32_t a) {
    asm volatile("ldmatrix.sync.aligned.m8n8.x4.trans.shared.b16 {%0,%1,%2,%3}, [%4];"
                 : "=r"(r[0]), "=r"(r[1]), "=r"(r[2]), "=r"(r[3]) : "r"(a) : "memory");
}
__device__ __forceinline__ void mma(float (&c)[4], const uint32_t (&a)[4], uint32_t b0, uint32_t b1) {
    asm volatile("mma.sync.aligned.m16n8k16.row.col.f32.bf16.bf16.f32 {%0,%1,%2,%3}, {%4,%5,%6,%7}, {%8,%9}, {%0,%1,%2,%3};"
                 : "+f"(c[0]), "+f"(c[1]), "+f"(c[2]), "+f"(c[3])
                 : "r"(a[0]), "r"(a[1]), "r"(a[2]), "r"(a[3]), "r"(b0), "r"(b1));
}
__device__ __forceinline__ uint32_t pack2(float lo, float hi) {
    uint32_t r; asm("cvt.rn.bf16x2.f32 %0, %1, %2;" : "=r"(r) : "f"(hi), "f"(lo)); return r;
}
__device__ __forceinline__ float bf_lo(uint32_t w) { return __uint_as_float(w << 16); }
__device__ __forceinline__ float bf_hi(uint32_t w) { return __uint_as_float(w & 0xFFFF0000u); }
__device__ __forceinline__ uint32_t hadd2(uint32_t a, uint32_t b) {
    uint32_t r; asm("add.rn.bf16x2 %0, %1, %2;" : "=r"(r) : "r"(a), "r"(b)); return r;
}
__device__ __forceinline__ float rbf(float x) { return bf_lo(pack2(x, 0.f)); }

__device__ __forceinline__ unsigned ticket(unsigned* p) {
    unsigned v; asm volatile("atom.relaxed.gpu.global.inc.u32 %0, [%1], %2;" : "=r"(v) : "l"(p), "n"(NTOT - 1) : "memory"); return v;
}
__device__ __forceinline__ void grid_barrier(unsigned* p, unsigned inc) {
    unsigned v;
    asm volatile("fence.acq_rel.gpu;\natom.relaxed.gpu.global.add.u32 %0, [%1], %2;" : "=r"(v) : "l"(p), "r"(inc) : "memory");
    const unsigned target = (v & ~8191u) + 8192u;
#pragma unroll 1
    for (int it = 0; it < (1 << 22); ++it) {
        asm volatile("ld.acquire.gpu.global.u32 %0, [%1];" : "=r"(v) : "l"(p) : "memory");
        if ((int)(v - target) >= 0) return;
    }
    __trap();
}
__device__ __forceinline__ void red4(float4* p, float a, float b, float c, float d) {
    asm volatile("red.relaxed.gpu.global.add.v4.f32 [%0], {%1,%2,%3,%4};" ::"l"(p), "f"(a), "f"(b), "f"(c), "f"(d) : "memory");
}
__device__ __forceinline__ uint4 ldrlx4(const void* p) {
    uint4 v; asm volatile("ld.relaxed.gpu.global.v4.u32 {%0,%1,%2,%3}, [%4];" : "=r"(v.x), "=r"(v.y), "=r"(v.z), "=r"(v.w) : "l"(p) : "memory");
    return v;
}
__device__ __forceinline__ float4 ldrlx4f(const float4* p) {
    float4 v; asm volatile("ld.relaxed.gpu.global.v4.f32 {%0,%1,%2,%3}, [%4];" : "=f"(v.x), "=f"(v.y), "=f"(v.z), "=f"(v.w) : "l"(p) : "memory");
    return v;
}
__device__ __forceinline__ void sts4(uint32_t a, float x, float y, float z, float w) {
    asm volatile("st.shared.v4.f32 [%0], {%1,%2,%3,%4};" ::"r"(a), "f"(x), "f"(y), "f"(z), "f"(w) : "memory");
}
__device__ __forceinline__ float4 lds4(uint32_t a) {
    float4 v; asm volatile("ld.shared.v4.f32 {%0,%1,%2,%3}, [%4];" : "=f"(v.x), "=f"(v.y), "=f"(v.z), "=f"(v.w) : "r"(a) : "memory");
    return v;
}
__device__ __forceinline__ void bar_sync(int id, int n) { asm volatile("bar.sync %0, %1;" ::"r"(id), "r"(n) : "memory"); }
__device__ __forceinline__ float wsum(float v) {
#pragma unroll
    for (int o = 16; o; o >>= 1) v += __shfl_xor_sync(~0u, v, o);
    return v;
}
__device__ __forceinline__ float wmax(float v) {
#pragma unroll
    for (int o = 16; o; o >>= 1) v = fmaxf(v, __shfl_xor_sync(~0u, v, o));
    return v;
}

enum { BAR_G = 1 };

__device__ __forceinline__ uint32_t pin(uint32_t v) { return __shfl_sync(~0u, v, threadIdx.x & 31); }
template <class T> __device__ __forceinline__ T* pin(T* p) {
    return reinterpret_cast<T*>(__shfl_sync(~0u, reinterpret_cast<unsigned long long>(p), threadIdx.x & 31));
}

__device__ __forceinline__ void poll6(const float4* p, int jstride, float count, float4 (&e)[6]) {
#pragma unroll 1
    for (int it = 0;; ++it) {
        bool ok = true;
#pragma unroll
        for (int i = 0; i < 6; ++i) ok = ok && e[i].w == count;
        if (__all_sync(~0u, ok)) break;
        if (it > (1 << 22)) __trap();
#pragma unroll
        for (int i = 0; i < 6; ++i)
            if (e[i].w != count) e[i] = ldrlx4f(p + (i >> 1) * jstride + (i & 1) * 4);
    }
}
__device__ __forceinline__ void pack6(const float4 (&e)[6], uint32_t (&bb)[8]) {
    bb[0] = pack2(e[0].x, e[1].x); bb[1] = pack2(e[0].y, e[1].y); bb[2] = pack2(e[0].z, e[1].z);
    bb[3] = pack2(e[2].x, e[3].x); bb[4] = pack2(e[2].y, e[3].y); bb[5] = pack2(e[2].z, e[3].z);
    bb[6] = pack2(e[4].x, e[5].x); bb[7] = pack2(e[4].y, e[5].y);
}
__device__ __forceinline__ void poll_frag(const float4* p, int jstride, float count, uint32_t (&bb)[8]) {
    float4 e[6];
#pragma unroll
    for (int i = 0; i < 6; ++i) e[i].w = -1.f;
    poll6(p, jstride, count, e);
    pack6(e, bb);
}

__device__ __forceinline__ void layernorm_frag(uint32_t (&v)[8], uint32_t ln, int w, int g, int t) {
    float s = 0.f;
#pragma unroll
    for (int i = 0; i < 8; ++i) s += bf_lo(v[i]) + bf_hi(v[i]);
    s += __shfl_xor_sync(~0u, s, 1); s += __shfl_xor_sync(~0u, s, 2);
    const float mw = s * (1.f / 64);
    float q0 = 0.f, q1 = 0.f;
#pragma unroll
    for (int i = 0; i < 8; ++i) {
        const float d0 = bf_lo(v[i]) - mw, d1 = bf_hi(v[i]) - mw;
        q0 = fmaf(d0, d0, q0); q1 = fmaf(d1, d1, q1);
    }
    q0 += q1;
    q0 += __shfl_xor_sync(~0u, q0, 1); q0 += __shfl_xor_sync(~0u, q0, 2);
    if (t == 0) asm volatile("st.shared.v2.f32 [%0], {%1,%2};" ::"r"(ln + g * 80 + w * 8), "f"(mw), "f"(q0) : "memory");
    bar_sync(BAR_G, NGT);
    float4 z[5];
#pragma unroll
    for (int i = 0; i < 5; ++i) z[i] = lds4(ln + g * 80 + i * 16);
    const float mean = ((z[0].x + z[0].z) + (z[1].x + z[1].z) + (z[2].x + z[2].z) + (z[3].x + z[3].z) + (z[4].x + z[4].z)) * 0.1f;
    float m2 = 0.f, d2 = 0.f;
#pragma unroll
    for (int i = 0; i < 5; ++i) {
        m2 += z[i].y + z[i].w;
        const float d0 = z[i].x - mean, d1 = z[i].z - mean;
        d2 = fmaf(d0, d0, d2); d2 = fmaf(d1, d1, d2);
    }
    const float var = rbf(fmaf(64.f, d2, m2) * (1.f / DM));
    const float mb = rbf(mean);
    float sd, rs;
    asm("sqrt.approx.f32 %0, %1;" : "=f"(sd) : "f"(rbf(var + 1e-5f)));
    asm("rcp.approx.f32 %0, %1;" : "=f"(rs) : "f"(rbf(sd)));
#pragma unroll
    for (int i = 0; i < 8; ++i) {
        const uint32_t d = pack2(bf_lo(v[i]) - mb, bf_hi(v[i]) - mb);
        v[i] = pack2(bf_lo(d) * rs, bf_hi(d) * rs);
    }
}

__device__ __forceinline__ void gemv64(uint32_t ab, uint32_t db, const uint32_t (&bb)[8]) {
    float acc[4][4] = {};
#pragma unroll
    for (int ks = 0; ks < 4; ++ks)
#pragma unroll
        for (int mt = 0; mt < 4; ++mt) {
            uint32_t a[4];
            ldsm4t(a, (ab ^ (mt << 5)) + ks * 2048);
            mma(acc[mt], a, bb[2 * ks], bb[2 * ks + 1]);
        }
    __syncwarp();
#pragma unroll
    for (int e = 0; e < 2; ++e) {
        const uint32_t d = db + e * 400;
        sts4(d, acc[0][e], acc[0][e + 2], acc[1][e], 0.f);
        sts4(d + 128, acc[1][e + 2], acc[2][e], acc[2][e + 2], 0.f);
        sts4(d + 256, acc[3][e], acc[3][e + 2], 0.f, 0.f);
    }
}

__global__ void __launch_bounds__(NTHREADS, 1)
fused_decode_kernel(const __grid_constant__ CUtensorMap tm_k, const __grid_constant__ CUtensorMap tm_v,
                    const __grid_constant__ CUtensorMap tm_wq, const __grid_constant__ CUtensorMap tm_wo,
                    const __grid_constant__ CUtensorMap tm_w1, const __grid_constant__ CUtensorMap tm_w2,
                    const __nv_bfloat16* __restrict__ x, __nv_bfloat16* __restrict__ out)
{
    extern __shared__ unsigned char smem_raw[];
    const uint32_t sb = ((uint32_t)__cvta_generic_to_shared(smem_raw) + 1023u) & ~1023u;
    const int warp = threadIdx.x >> 5, lane = threadIdx.x & 31;
    const int cta = blockIdx.x;
    const uint32_t bars = sb + SM_BAR;
    const int f2 = cta - (NCTA - NCTA_F2);

    const int g = lane >> 2, t = lane & 3;
    const int mi = lane >> 3, r = lane & 7;
    const int w = warp - GW0, tid = threadIdx.x - GW0 * 32;
    unsigned nxt = 0, tag = 0;
    if (threadIdx.x == 0) {
        mbar_init(bars + B_WQ * 8, 1); mbar_init(bars + B_WQ * 8 + 8, 1); mbar_init(bars + B_FULL * 8, 1);
        asm volatile("fence.mbarrier_init.release.cluster;" ::: "memory");
        if (cta < NCTA_Q) {
            mbar_expect_tx(bars + B_WQ * 8, 40960);
            tma2d_ef(sb + SM_WQ, &tm_wq, cta * 64, 0, bars + B_WQ * 8);
            tma2d_ef(sb + SM_WQ + 20480, &tm_wq, cta * 64, 160, bars + B_WQ * 8);
            mbar_expect_tx(bars + B_WQ * 8 + 8, 40960);
            tma2d_ef(sb + SM_WQ + 40960, &tm_wq, cta * 64, 320, bars + B_WQ * 8 + 8);
            tma2d_ef(sb + SM_WQ + 61440, &tm_wq, cta * 64, 480, bars + B_WQ * 8 + 8);
        }
        mbar_expect_tx(bars + B_FULL * 8, UNIT_BYTES);
        tma2d_ef(sb + SM_RING, &tm_k, 0, (int)(((cta >> 4) * SK + (SK - WIN) + (cta & 15) * 64) * 3), bars + B_FULL * 8);
    }
    if (threadIdx.x == 32) {
        mbar_init(bars + B_X * 8, 1);
        asm volatile("fence.mbarrier_init.release.cluster;" ::: "memory");
        mbar_expect_tx(bars + B_X * 8, 8 * DM * 2);
        asm volatile("cp.async.bulk.shared::cluster.global.mbarrier::complete_tx::bytes [%0], [%1], %2, [%3];"
                     ::"r"(sb + SM_RED), "l"(x), "r"(8 * DM * 2), "r"(bars + B_X * 8) : "memory");
    }
    if (threadIdx.x == 64) {
        nxt = ticket(&g_s.ctr[C_TICKET]);
        asm volatile("ld.relaxed.gpu.global.u32 %0, [%1];" : "=r"(tag) : "l"(&g_s.ctr[C_S1A]) : "memory");
    }
    if (warp >= 3 && lane < 3) {
        const int i = (warp - 3) * 3 + lane;
        if (i < B_COUNT && i != B_FULL && (i < B_WQ || i > B_X)) mbar_init(bars + i * 8, (i == B_KA || i == B_KB) ? NCW : 1);
        asm volatile("fence.mbarrier_init.release.cluster;" ::: "memory");
    }
    __syncthreads();
    if (threadIdx.x == 64) {
        asm volatile("st.shared.v2.u32 [%0], {%1,%2};" ::"r"(sb + SM_META + 40), "r"(nxt), "r"(tag | 8191u) : "memory");
        mbar_arrive(bars + B_TAG * 8);
    }

    if (warp == 0) {
        if (lane == 0) {
            asm volatile("st.shared.u32 [%0], %1;" ::"r"(sb + SM_META), "r"(cta) : "memory");
            mbar_arrive(bars + B_META * 8);
            mbar_wait(bars + B_TAG * 8, 0);
            asm volatile("ld.shared.u32 %0, [%1];" : "=r"(nxt) : "r"(sb + SM_META + 40) : "memory");
            bool told = false;
            int i = 1;
#pragma unroll 1
            for (;; ++i) {
                const int s = i & (NST - 1);
                const unsigned u = nxt + NCTA;
                if (u >= NU && !told) {
                    told = true;
                    asm volatile("st.shared.u32 [%0], %1;" ::"r"(sb + SM_META + 36), "r"(i) : "memory");
                    mbar_arrive(bars + B_DONE * 8);
                }
                if (u >= NTOT) break;
                const unsigned uu = u & (NKU - 1);
                const CUtensorMap* tm = u < NKU ? &tm_k : !told ? &tm_v : &tm_wo;
                const int c0 = !told ? 0 : (uu % 10) * 64;
                const int c1 = !told ? (int)(((uu >> 4) * SK + (SK - WIN) + (uu & 15) * 64) * 3) : (uu / 10) * DH;
                const int nf = u >= NTOT - ENDZ ? NFLIGHT + 1 : NFLIGHT;
                if (i >= nf) mbar_wait(bars + (B_FULL + ((i - nf) & (NST - 1))) * 8, ((i - nf) >> 3) & 1);
                else if (cta < NCTA_Q) mbar_wait(bars + B_WQ * 8, 0);
                {
                    const unsigned c = clock();
                    while ((int)(clock() - c) < PD) {}
                }
                if (i >= NST) mbar_wait(bars + (B_EMPTY + s) * 8, ((i >> 3) - 1) & 1);
                else if (i == 5) mbar_wait(bars + B_WBFREE * 8, 0);
                asm volatile("st.shared.u32 [%0], %1;" ::"r"(sb + SM_META + s * 4), "r"(u) : "memory");
                mbar_arrive(bars + (B_META + s) * 8);
                mbar_expect_tx(bars + (B_FULL + s) * 8, UNIT_BYTES);
                tma2d_ef(sb + SM_RING + s * UNIT_BYTES, tm, c0, c1, bars + (B_FULL + s) * 8);
                nxt = ticket(&g_s.ctr[C_TICKET]);
                if (i == 16) {
                    asm volatile("prefetch.tensormap [%0];" ::"l"(&tm_v) : "memory");
                    asm volatile("prefetch.tensormap [%0];" ::"l"(&tm_wo) : "memory");
                }
            }
            asm volatile("st.shared.u32 [%0], %1;" ::"r"(sb + SM_META + 32), "r"(i) : "memory");
            mbar_arrive(bars + B_TAIL * 8);
#pragma unroll 1
            for (int j = i; j < i + NCW; ++j) {
                mbar_wait(bars + (B_EMPTY + (j & (NST - 1))) * 8, ((j >> 3) - 1) & 1);
                asm volatile("st.shared.u32 [%0], %1;" ::"r"(sb + SM_META + (j & (NST - 1)) * 4), "r"(END) : "memory");
                mbar_arrive(bars + (B_META + (j & (NST - 1))) * 8);
            }
        }
        return;
    }

    if (warp < GW0) {
        uint32_t ka[3], va[3];
        {
            const int key = (mi & 1) ? 8 + ((r + 4) & 7) : r, hi = mi >> 1;
            const int gg = (r >> 1) + 4 * (mi >> 1);
            const int vkey = (r & 1) ? 8 + ((gg + 4) & 7) : gg, vhi = mi & 1;
#pragma unroll
            for (int th = 0; th < 3; ++th) {
                ka[th] = (key * 3 + th) * 128 + ((hi ^ ((key * 3 + th) & 7)) << 4);
                va[th] = (vkey * 3 + th) * 128 + ((vhi ^ ((vkey * 3 + th) & 7)) << 4);
            }
        }
        mbar_wait(bars + B_TAG * 8, 0);
        asm volatile("ld.shared.u32 %0, [%1];" : "=r"(tag) : "r"(sb + SM_META + 44) : "memory");
        mbar_wait(bars + B_WBFREE * 8, 0);
        int phase = 0;
#pragma unroll 1
        for (int i = warp - 1;; i += NCW) {
            const int s = i & (NST - 1);
            const uint32_t par = (i >> 3) & 1;
            const uint32_t stage = sb + SM_RING + s * UNIT_BYTES;
            mbar_wait(bars + (B_META + s) * 8, par);
            unsigned u;
            asm volatile("ld.shared.u32 %0, [%1];" : "=r"(u) : "r"(sb + SM_META + s * 4) : "memory");
            const int ph = u >> 11;
            if (ph != phase) {
                __syncwarp();
                if (lane == 0) {
                    if (phase < 1) mbar_arrive(bars + B_KA * 8);
                    if (phase < 2 && ph >= 2) mbar_arrive(bars + B_KB * 8);
                }
                if (ph >= 4) break;
                if (ph >= 2) mbar_wait(bars + (ph == 2 ? B_OKA : B_OKB) * 8, 0);
                phase = ph;
            }
            const unsigned item = (u & (NKU - 1)) >> 4, chunk = u & 15;
            if (u < NKU) {
                uint32_t qf[24];
                const uint4* qp = g_s.q + item * 36 + t * 9;
#pragma unroll 1
                for (int it = 0;; ++it) {
                    bool ok = true;
#pragma unroll
                    for (int j = 0; j < 9; ++j) {
                        const uint4 v = ldrlx4(qp + j);
                        const int c = (j / 3) * 8 + (j % 3) * 3;
                        qf[c] = v.x; qf[c + 1] = v.y;
                        if (j % 3 < 2) qf[c + 2] = v.z;
                        ok = ok && v.w == tag;
                    }
                    if (__all_sync(~0u, ok)) break;
                    if (it > (1 << 22)) __trap();
                    __nanosleep(100);
                }
                mbar_wait(bars + (B_FULL + s) * 8, par);
                float acc[4][4] = {};
#pragma unroll
                for (int ks = 0; ks < 12; ++ks) {
                    const uint32_t a0 = stage + (ka[ks >> 2] ^ ((ks & 3) << 5));
#pragma unroll
                    for (int kt = 0; kt < 4; ++kt) {
                        uint32_t a[4];
                        ldsm4(a, a0 + kt * 6144);
                        mma(acc[kt], a, qf[2 * ks], qf[2 * ks + 1]);
                    }
                }
                float s0 = t == 0 ? acc[0][0] : t == 1 ? acc[1][0] : t == 2 ? acc[2][0] : acc[3][0];
                float s1 = t == 0 ? acc[0][2] : t == 1 ? acc[1][2] : t == 2 ? acc[2][2] : acc[3][2];
                const float scale = 0.07216878364870322f;
                uint32_t w = pack2(s0, s1);
                __syncwarp();
                if (lane == 0) mbar_arrive(bars + (B_EMPTY + s) * 8);
                w = pack2(bf_lo(w) * scale, bf_hi(w) * scale);
                s0 = bf_lo(w); s1 = bf_hi(w);
                const float m = wmax(fmaxf(s0, s1));
                const float l = wsum(__expf(s0 - m) + __expf(s1 - m));
                g_s.sc[(item * 16 + chunk) * 32 + lane] = w;
                if (lane == 0) g_s.stats[item * 16 + chunk] = make_float2(m, l);
            } else {
                uint32_t w; float2 st;
                asm volatile("ld.global.cg.u32 %0, [%1];" : "=r"(w) : "l"(g_s.sc + (item * 16 + chunk) * 32 + lane) : "memory");
                asm volatile("ld.global.cg.v2.f32 {%0,%1}, [%2];" : "=f"(st.x), "=f"(st.y) : "l"(g_s.stats + item * 16 + (lane & 15)) : "memory");
                const float m = wmax(st.x);
                const float rl = __fdividef(2.f, wsum(st.y * __expf(st.x - m)));
                const uint32_t p = pack2(__expf(bf_lo(w) - m) * rl, __expf(bf_hi(w) - m) * rl);
                uint32_t pb[8];
#pragma unroll
                for (int kt = 0; kt < 4; ++kt) {
                    pb[2 * kt] = __shfl_sync(~0u, p, 4 * t + kt);
                    pb[2 * kt + 1] = __shfl_sync(~0u, p, 16 + 4 * t + kt);
                }
                mbar_wait(bars + (B_FULL + s) * 8, par);
                float acc[12][4] = {};
#pragma unroll
                for (int kt = 0; kt < 4; ++kt) {
#pragma unroll
                    for (int dt = 0; dt < 12; ++dt) {
                        uint32_t a[4];
                        ldsm4t(a, stage + (va[dt >> 2] ^ ((dt & 3) << 5)) + kt * 6144);
                        mma(acc[dt], a, pb[2 * kt], pb[2 * kt + 1]);
                    }
                }
                float o[8];
#pragma unroll
                for (int j = 0; j < 4; ++j) {
                    o[2 * j] = t == 0 ? acc[j][0] : t == 1 ? acc[4 + j][0] : acc[8 + j][0];
                    o[2 * j + 1] = t == 0 ? acc[j][2] : t == 1 ? acc[4 + j][2] : acc[8 + j][2];
                }
                if (t < 3) {
                    float4* op = g_s.o_acc + item * 72 + t * 8 + (g & 1) * 4 + (g >> 1);
                    red4(op, o[0], o[1], o[2], 1.f);
                    red4(op + 24, o[3], o[4], o[5], 1.f);
                    red4(op + 48, o[6], o[7], 0.f, 1.f);
                }
                __syncwarp();
                if (lane == 0) mbar_arrive(bars + (B_EMPTY + s) * 8);
            }
        }
        return;
    }

    {
        constexpr int NH4 = 8 * 240, NU4 = 48 * 32, NALL = NH4 + NU4 + 256 * 72;
#pragma unroll 1
        for (int i = cta * NGT + tid; i < NALL; i += NCTA * NGT) {
            const unsigned f = (i >= NH4 && i < NH4 + NU4) ? SENT : 0u;
            reinterpret_cast<uint4*>(g_s.h_acc)[i] = make_uint4(f, f, f, f);
        }
    }
    const uint32_t red = sb + SM_RED, ln = sb + SM_LN;
    uint32_t xr[8], xres;
    mbar_wait(bars + B_X * 8, 0);
#pragma unroll
    for (int c = 0; c < 8; ++c)
        asm volatile("ld.shared.u32 %0, [%1];" : "=r"(xr[c]) : "r"(red + (g * DM + w * 64 + c * 8 + 2 * t) * 2) : "memory");
    asm volatile("ld.shared.u16 %0, [%1];" : "=r"(xres) : "r"(red + ((2 * t + (w & 1)) * DM + max(f2, 0) * 16 + ((w >> 1) & 1) * 8 + g) * 2) : "memory");
    const int rb = tid / 24, rj = tid % 24;
    const uint32_t a_off = ((mi >> 1) * 8 + r) * 128 + (((mi & 1) ^ r) << 4), d_off = t * 800 + g * 16;
    if (cta < NCTA_Q) {
        uint32_t bb[8];
#pragma unroll
        for (int c = 0; c < 8; ++c) bb[c] = xr[c];
        layernorm_frag(bb, ln, w, g, t);
        mbar_wait(bars + (B_WQ + (w >= 5)) * 8, 0);
        gemv64(sb + SM_WQ + w * 8192 + a_off, sb + SM_WQ + w * 8192 + d_off, bb);
        bar_sync(BAR_G, NGT);
        if (tid < 192) {
            float s0 = 0.f, s1 = 0.f, s2 = 0.f;
#pragma unroll
            for (int k = 0; k < NGW; ++k) {
                const float4 v = lds4(sb + SM_WQ + k * 8192 + rb * 400 + rj * 16);
                s0 += v.x; s1 += v.y; s2 += v.z;
            }
            const float n0 = __shfl_xor_sync(~0u, s0, 1), n1 = __shfl_xor_sync(~0u, s1, 1), n2 = __shfl_xor_sync(~0u, s2, 1);
            if (!(rj & 1)) {
                mbar_wait(bars + B_TAG * 8, 0);
                asm volatile("ld.shared.u32 %0, [%1];" : "=r"(tag) : "r"(sb + SM_META + 44) : "memory");
                asm volatile("st.relaxed.gpu.global.v4.u32 [%0], {%1,%2,%3,%4};"
                             ::"l"(g_s.q + (rb * NH + cta / 3) * 36 + ((rj & 7) >> 1) * 9 + (cta % 3) * 3 + (rj >> 3)),
                               "r"(pack2(s0, n0)), "r"(pack2(s1, n1)), "r"(pack2(s2, n2)), "r"(tag) : "memory");
            }
        }
        asm volatile("fence.proxy.async.shared::cta;" ::: "memory");
    }
    bar_sync(BAR_G, NGT);
    if (tid == 0) {
        const unsigned inc = cta == 0 ? 8193u - NCTA : 1u;
        mbar_arrive(bars + B_WBFREE * 8);
        mbar_wait(bars + B_KA * 8, 0);
        grid_barrier(&g_s.ctr[C_S1A], inc);
        mbar_arrive(bars + B_OKA * 8);
        mbar_wait(bars + B_KB * 8, 0);
        grid_barrier(&g_s.ctr[C_S1B], inc);
        mbar_arrive(bars + B_OKB * 8);
        mbar_wait(bars + B_DONE * 8, 0);
    }
    __syncwarp();
    bar_sync(BAR_G, NGT);
    if (w < 9) {
        const int grp = w / 3, th = w % 3, gt = tid - grp * 96;
        unsigned i;
        asm volatile("ld.shared.u32 %0, [%1];" : "=r"(i) : "r"(sb + SM_META + 36) : "memory");
#pragma unroll 1
        for (i += grp;; i += 3) {
            const int s = i & (NST - 1);
            const uint32_t par = (i >> 3) & 1;
            unsigned u;
            mbar_wait(bars + (B_META + s) * 8, par);
            asm volatile("ld.shared.u32 %0, [%1];" : "=r"(u) : "r"(sb + SM_META + s * 4) : "memory");
            if (u == END) break;
            const unsigned head = (u - NU) / 10, nt = (u - NU) % 10;
            uint32_t bb[8];
            poll_frag(pin(g_s.o_acc + (g * NH + head) * 72 + th * 8 + t), 24, 16.f, bb);
            const uint32_t stage = sb + SM_RING + s * UNIT_BYTES;
            const int rb0 = gt / 24, rj0 = gt % 24;
            float4* hp = pin(g_s.h_acc + rb0 * 240 + nt * 24 + (rj0 & 24) + (rj0 & 1) * 4 + ((rj0 & 7) >> 1));
            const uint32_t ab = pin(stage + th * 8192 + a_off), db = pin(stage + th * 8192 + d_off);
            const uint32_t ra = pin(stage + rb0 * 400 + rj0 * 16);
            mbar_wait(bars + (B_FULL + s) * 8, par);
            gemv64(ab, db, bb);
            bar_sync(3 + grp, 96);
#pragma unroll
            for (int e = 0; e < 2; ++e) {
                const float4 v0 = lds4(ra + e * 1600), v1 = lds4(ra + e * 1600 + 8192), v2 = lds4(ra + e * 1600 + 16384);
                red4(hp + e * 960, v0.x + v1.x + v2.x, v0.y + v1.y + v2.y, v0.z + v1.z + v2.z, 1.f);
            }
            bar_sync(3 + grp, 96);
            asm volatile("fence.proxy.async.shared::cta;" ::: "memory");
            bar_sync(3 + grp, 96);
            if (gt == 0) mbar_arrive(bars + (B_EMPTY + s) * 8);
        }
    } else {
        const bool is_w1 = cta < NCTA_F1;
        const CUtensorMap* tm = is_w1 ? &tm_w1 : &tm_w2;
        if (lane == 0) asm volatile("prefetch.tensormap [%0];" ::"l"(tm) : "memory");
        mbar_wait(bars + B_TAIL * 8, 0);
        if (lane == 0 && (is_w1 || f2 >= 0)) {
            const unsigned c = clock();
            const int c0 = is_w1 ? cta * 32 : f2 * 16, nf = is_w1 ? 3 : 1;
            const uint32_t bytes = is_w1 ? 20480 : 24576;
            unsigned i;
            asm volatile("ld.shared.u32 %0, [%1];" : "=r"(i) : "r"(sb + SM_META + 32) : "memory");
            const uint32_t f0 = bars + (B_FULL + (i & 7)) * 8, f1 = bars + (B_FULL + ((i + 1) & 7)) * 8;
            mbar_wait(bars + (B_EMPTY + (i & 7)) * 8, ((i >> 3) - 1) & 1);
            mbar_expect_tx(f0, bytes);
            mbar_wait(bars + (B_EMPTY + ((i + 1) & 7)) * 8, (((i + 1) >> 3) - 1) & 1);
            mbar_expect_tx(f1, bytes);
            mbar_wait(bars + (B_FULL + ((i - nf) & 7)) * 8, ((i - nf) >> 3) & 1);
            if (is_w1) {
                while ((int)(clock() - c) < W1D) {
                    uint32_t ok;
                    asm volatile("{\n.reg .pred p;\nmbarrier.test_wait.parity.shared::cta.b64 p, [%1], %2;\nselp.u32 %0, 1, 0, p;\n}"
                                 : "=r"(ok) : "r"(bars + (B_FULL + ((i - 1) & 7)) * 8), "r"(((i - 1) >> 3) & 1) : "memory");
                    if (ok) break;
                }
            } else {
                const unsigned c2 = clock();
                while ((int)(clock() - c2) < W2D) {}
            }
            tma3d(sb + SM_RING + (i & 7) * UNIT_BYTES, tm, c0, 0, f0);
            tma3d(sb + SM_RING + ((i + 1) & 7) * UNIT_BYTES, tm, c0, is_w1 ? 2 : 3, f1);
        }
        __syncwarp();
    }
    unsigned tail;
    asm volatile("ld.shared.u32 %0, [%1];" : "=r"(tail) : "r"(sb + SM_META + 32) : "memory");
    if (cta < NCTA_F1) {
        constexpr uint32_t ONES = 0x3F803F80u;
        uint32_t a[8][4];
        const unsigned i1 = tail + (w >= 5);
        const uint32_t ab = pin(sb + SM_RING + (i1 & 7) * UNIT_BYTES + ((w % 5) * 64 + (mi >> 1) * 8 + r) * 64 + (((mi & 1) ^ (r >> 1)) << 4));
        unsigned* up = pin(reinterpret_cast<unsigned*>(g_s.u + cta * 32 + 8 * t + (w & 1) * 4 + (g & 3)) + (w & 2) + (g >> 2));
        const float4* hp = pin(g_s.h_acc + g * 240 + w * 24 + t);
        const uint32_t pw = pin(red + w * 1024 + lane * 8), pr = pin(red + w * 256 + lane * 8);
        const uint32_t cw = pin(red + 10240 + w * 128 + g * 8), cr = pin(red + 10240 + ((w >> 1) & 1) * 64 + g * 8);
        const uint32_t lw = pin(ln + g * 80 + w * 8), lr = pin(ln + (2 * t + (w & 1)) * 80);
        float cnt;
#pragma unroll 1
        for (int it = 0;; ++it) {
            cnt = ldrlx4f(g_s.h_acc + 7 * 240 + w * 24 + 23).w;
            uint32_t ok;
            asm volatile("{\n.reg .pred p;\nmbarrier.try_wait.parity.shared::cta.b64 p, [%1], %2, %3;\nselp.u32 %0, 1, 0, p;\n}"
                         : "=r"(ok) : "r"(bars + (B_FULL + (i1 & 7)) * 8), "r"((i1 >> 3) & 1), "r"(250) : "memory");
            if (__any_sync(~0u, ok)) break;
            if (__shfl_sync(~0u, cnt, 0) >= 32.f) break;
            if (it > (1 << 22)) __trap();
        }
        float4 e[6];
#pragma unroll
        for (int i = 0; i < 6; ++i) e[i] = ldrlx4f(hp + (i >> 1) * 8 + (i & 1) * 4);
        mbar_wait(bars + (B_FULL + (i1 & 7)) * 8, (i1 >> 3) & 1);
#pragma unroll
        for (int ks = 0; ks < 4; ++ks) { ldsm4t(a[2 * ks], ab + ks * 1024); ldsm4t(a[2 * ks + 1], (ab ^ 32) + ks * 1024); }
        float cs[2][4] = {};
#pragma unroll
        for (int ks = 0; ks < 4; ++ks) { mma(cs[0], a[2 * ks], ONES, ONES); mma(cs[1], a[2 * ks + 1], ONES, ONES); }
        if (t == 0) {
            asm volatile("st.shared.v2.f32 [%0], {%1,%2};" ::"r"(cw), "f"(cs[0][0]), "f"(cs[0][2]) : "memory");
            asm volatile("st.shared.v2.f32 [%0], {%1,%2};" ::"r"(cw + 64), "f"(cs[1][0]), "f"(cs[1][2]) : "memory");
        }
        uint32_t bb[8];
        const float full = __uint_as_float(0x42000000u | ((__float_as_uint(cs[0][0]) ^ __float_as_uint(cs[1][0]) ^ __float_as_uint(cnt) ^
                                                            __float_as_uint(e[4].z) ^ __float_as_uint(e[5].z)) & (tail >> 16)));
        poll6(hp, 8, full, e);
        pack6(e, bb);
        float acc[3][4] = {};
#pragma unroll
        for (int ks = 0; ks < 4; ++ks) {
            const uint32_t h0 = hadd2(xr[2 * ks], bb[2 * ks]), h1 = hadd2(xr[2 * ks + 1], bb[2 * ks + 1]);
            const uint32_t ha[4] = {h0, ONES, h1, ONES};
            mma(acc[0], a[2 * ks], h0, h1);
            mma(acc[1], a[2 * ks + 1], h0, h1);
            mma(acc[2], ha, h0, h1);
        }
#pragma unroll
        for (int j = 0; j < 4; ++j)
            asm volatile("st.shared.v2.f32 [%0], {%1,%2};" ::"r"(pw + j * 256), "f"(acc[j >> 1][j & 1]), "f"(acc[j >> 1][(j & 1) + 2]) : "memory");
        if ((g >> 1) == t)
            asm volatile("st.shared.v2.f32 [%0], {%1,%2};" ::"r"(lw), "f"((g & 1) ? acc[2][3] : acc[2][2]),
                         "f"((g & 1) ? acc[2][1] : acc[2][0]) : "memory");
        bar_sync(BAR_G, NGT);
        if (w < 4) {
            float4 v[NGW], z[5];
#pragma unroll
            for (int i = 0; i < 5; ++i) z[i] = lds4(lr + i * 16);
#pragma unroll
            for (int k = 0; k < NGW; ++k) {
                asm volatile("ld.shared.v2.f32 {%0,%1}, [%2];" : "=f"(v[k].x), "=f"(v[k].y) : "r"(pr + k * 1024) : "memory");
                asm volatile("ld.shared.v2.f32 {%0,%1}, [%2];" : "=f"(v[k].z), "=f"(v[k].w) : "r"(cr + k * 128) : "memory");
            }
            const float mean = (((z[0].x + z[0].z) + (z[1].x + z[1].z)) + ((z[2].x + z[2].z) + (z[3].x + z[3].z)) + (z[4].x + z[4].z)) * (1.f / DM);
            const float msq = (((z[0].y + z[0].w) + (z[1].y + z[1].w)) + ((z[2].y + z[2].w) + (z[3].y + z[3].w)) + (z[4].y + z[4].w)) * (1.f / DM);
            const float var = rbf(fmaxf(fmaf(-mean, mean, msq), 0.f));
            const float mb = rbf(mean);
            float sd, rs;
            asm("sqrt.approx.ftz.f32 %0, %1;" : "=f"(sd) : "f"(rbf(var + 1e-5f)));
            asm("rcp.approx.ftz.f32 %0, %1;" : "=f"(rs) : "f"(rbf(sd)));
#pragma unroll
            for (int k = 0; k < 5; ++k) { v[k].x += v[k + 5].x; v[k].y += v[k + 5].y; v[k].z += v[k + 5].z; v[k].w += v[k + 5].w; }
            const float a0 = ((v[0].x + v[1].x) + (v[2].x + v[3].x)) + v[4].x, a1 = ((v[0].y + v[1].y) + (v[2].y + v[3].y)) + v[4].y;
            const float c0 = ((v[0].z + v[1].z) + (v[2].z + v[3].z)) + v[4].z, c1 = ((v[0].w + v[1].w) + (v[2].w + v[3].w)) + v[4].w;
            const uint32_t zz = pack2(fmaf(-mb, c0, a0) * rs, fmaf(-mb, c1, a1) * rs);
            const float z0 = bf_lo(zz), z1 = bf_hi(zz);
            float e0, e1;
            asm("ex2.approx.ftz.f32 %0, %1;" : "=f"(e0) : "f"(z0 * -1.4426950408889634f));
            asm("ex2.approx.ftz.f32 %0, %1;" : "=f"(e1) : "f"(z1 * -1.4426950408889634f));
            asm("rcp.approx.ftz.f32 %0, %1;" : "=f"(e0) : "f"(1.f + e0));
            asm("rcp.approx.ftz.f32 %0, %1;" : "=f"(e1) : "f"(1.f + e1));
            asm volatile("st.relaxed.gpu.global.u32 [%0], %1;" ::"l"(up), "r"(pack2(z0 * e0, z1 * e1)) : "memory");
        }
    } else if (f2 >= 0 && w < 8) {
        uint32_t a[12][4];
        const unsigned i2 = tail + (w >> 2);
        mbar_wait(bars + (B_FULL + (i2 & 7)) * 8, (i2 >> 3) & 1);
        {
            const int row = (mi >> 1) * 4 + (r >> 1) + (r & 1) * 8;
            const uint32_t ab = sb + SM_RING + (i2 & 7) * UNIT_BYTES + ((w & 3) * 192 + row) * 32 + (((mi & 1) ^ ((row >> 2) & 1)) << 4);
#pragma unroll
            for (int ks = 0; ks < 12; ++ks) ldsm4t(a[ks], ab + ks * 512);
        }
        float hres = 0.f;
        __nv_bfloat16* op = pin(out + (2 * t + (w & 1)) * DM + f2 * 16 + ((w >> 1) & 1) * 8 + g);
        const uint4* up = pin(g_s.u + w * 6 * 32 + lane);
        const uint32_t pw = pin(red + w * 512 + lane * 4), pr = pin(red + w * 128 + lane * 4);
        if (w < 4) {
            const int ch = (f2 & 3) * 2 + (w >> 1);
            const float4* hp = pin(g_s.h_acc + (2 * t + (w & 1)) * 240 + (f2 >> 2) * 24 + (ch / 3) * 8 + (g & 1) * 4 + (g >> 1));
            float4 v = make_float4(0.f, 0.f, 0.f, -1.f);
#pragma unroll 1
            for (int it = 0;; ++it) {
                if (v.w != 32.f) v = ldrlx4f(hp);
                if (__all_sync(~0u, v.w == 32.f)) break;
                if (it > (1 << 22)) __trap();
            }
            hres = rbf(bf_lo(xres) + rbf(ch % 3 == 0 ? v.x : ch % 3 == 1 ? v.y : v.z));
        }
        bar_sync(2, 256);
        uint4 uu[6];
        unsigned mx[6];
#pragma unroll
        for (int i = 0; i < 6; ++i) { uu[i] = make_uint4(0u, 0u, 0u, 0u); mx[i] = SENT; }
#pragma unroll 1
        for (int it = 0;; ++it) {
#pragma unroll
            for (int i = 0; i < 6; ++i)
                if (mx[i] == SENT) uu[i] = ldrlx4(up + i * 32);
#pragma unroll
            for (int i = 0; i < 6; ++i) mx[i] = max(max(uu[i].x, uu[i].y), max(uu[i].z, uu[i].w));
            if (__all_sync(~0u, max(max(max(mx[0], mx[1]), max(mx[2], mx[3])), max(mx[4], mx[5])) != SENT)) break;
            if (it > (1 << 22)) __trap();
        }
        float acc[4][4] = {};
#pragma unroll
        for (int i = 0; i < 6; ++i) {
            mma(acc[(2 * i) & 3], a[2 * i], uu[i].x, uu[i].y);
            mma(acc[(2 * i + 1) & 3], a[2 * i + 1], uu[i].z, uu[i].w);
        }
#pragma unroll
        for (int c = 0; c < 4; ++c)
            asm volatile("st.shared.f32 [%0], %1;" ::"r"(pw + c * 128),
                         "f"((acc[0][c] + acc[1][c]) + (acc[2][c] + acc[3][c])) : "memory");
        bar_sync(2, 256);
        if (w < 4) {
            float v[8];
#pragma unroll
            for (int k = 0; k < 8; ++k)
                asm volatile("ld.shared.f32 %0, [%1];" : "=f"(v[k]) : "r"(pr + k * 512) : "memory");
            const uint32_t res = pack2(hres + rbf(((v[0] + v[1]) + (v[2] + v[3])) + ((v[4] + v[5]) + (v[6] + v[7]))), 0.f);
            asm volatile("st.global.u16 [%0], %1;" ::"l"(op), "h"((unsigned short)res) : "memory");
        }
    }
}

typedef CUresult (*EncodeFn)(CUtensorMap*, CUtensorMapDataType, cuuint32_t, void*, const cuuint64_t*, const cuuint64_t*,
                             const cuuint32_t*, const cuuint32_t*, CUtensorMapInterleave, CUtensorMapSwizzle,
                             CUtensorMapL2promotion, CUtensorMapFloatOOBfill);

void make_map(EncodeFn enc, CUtensorMap* m, void* base, uint64_t cols, uint64_t rows, uint32_t bc, uint32_t br,
              uint32_t bo, CUtensorMapSwizzle sw) {
    cuuint64_t dims[3] = {cols, bo ? br : rows, rows / br};
    cuuint64_t strides[2] = {cols * 2, cols * 2 * br};
    cuuint32_t box[3] = {bc, br, bo};
    cuuint32_t es[3] = {1, 1, 1};
    enc(m, CU_TENSOR_MAP_DATA_TYPE_BFLOAT16, bo ? 3 : 2, base, dims, strides, box, es, CU_TENSOR_MAP_INTERLEAVE_NONE, sw,
        CU_TENSOR_MAP_L2_PROMOTION_L2_128B, CU_TENSOR_MAP_FLOAT_OOB_FILL_NONE);
}

struct FallbackScratch { float a[8 * DM], q[8 * NH * DH], o[8 * NH * DH], h[8 * DM], u[8 * FF]; };
__device__ FallbackScratch g_f;

__global__ void fb_ln(const __nv_bfloat16* xb, const float* xf, float* y) {
    float v[20], s = 0.f, q = 0.f;
    for (int i = 0; i < 20; ++i) {
        const int k = blockIdx.x * DM + i * 32 + threadIdx.x;
        v[i] = xb ? __bfloat162float(xb[k]) : xf[k];
        s += v[i];
    }
    const float mean = wsum(s) / DM;
    for (int i = 0; i < 20; ++i) q += (v[i] - mean) * (v[i] - mean);
    const float sd = rbf(sqrtf(rbf(rbf(wsum(q) / DM) + 1e-5f))), mb = rbf(mean);
    for (int i = 0; i < 20; ++i) y[blockIdx.x * DM + i * 32 + threadIdx.x] = rbf(rbf(v[i] - mb) / sd);
}
__global__ void fb_gemv(const float* a, const __nv_bfloat16* wt, int K, int N, int mode, const void* res, void* y) {
    const int n = blockIdx.x * blockDim.x + threadIdx.x, b = blockIdx.y;
    float s = 0.f;
    for (int k = 0; k < K; ++k) s = fmaf(a[b * K + k], __bfloat162float(wt[(size_t)k * N + n]), s);
    s = rbf(s);
    if (mode == 1) s = rbf(s / (1.f + expf(-s)));
    if (mode == 2) s = rbf(__bfloat162float(static_cast<const __nv_bfloat16*>(res)[b * N + n]) + s);
    if (mode == 3) static_cast<__nv_bfloat16*>(y)[b * N + n] = __float2bfloat16(static_cast<const float*>(res)[b * N + n] + s);
    else static_cast<float*>(y)[b * N + n] = s;
}
__global__ void fb_attn(const float* q, const __nv_bfloat16* kc, const __nv_bfloat16* vc, float* o) {
    __shared__ float p[WIN];
    const size_t base = ((size_t)blockIdx.x * SK + (SK - WIN)) * DH;
    for (int j = threadIdx.x; j < WIN; j += DH) {
        float s = 0.f;
        for (int d = 0; d < DH; ++d) s = fmaf(q[blockIdx.x * DH + d], __bfloat162float(kc[base + (size_t)j * DH + d]), s);
        p[j] = rbf(rbf(s) * 0.07216878364870322f);
    }
    __syncthreads();
    float m = p[0], l = 0.f, acc = 0.f;
    for (int j = 1; j < WIN; ++j) m = fmaxf(m, p[j]);
    for (int j = 0; j < WIN; ++j) l += expf(p[j] - m);
    for (int j = 0; j < WIN; ++j) acc = fmaf(rbf(expf(p[j] - m) / l), __bfloat162float(vc[base + (size_t)j * DH + threadIdx.x]), acc);
    o[blockIdx.x * DH + threadIdx.x] = rbf(acc);
}
void fallback_launch(void* const* d_in, void* d_out, cudaStream_t st) {
    FallbackScratch* f = nullptr;
    cudaGetSymbolAddress(reinterpret_cast<void**>(&f), g_f);
    typedef const __nv_bfloat16* BP;
    fb_ln<<<8, 32, 0, st>>>((BP)d_in[0], nullptr, f->a);
    fb_gemv<<<dim3(NH * DH / 128, 8), 128, 0, st>>>(f->a, (BP)d_in[3], DM, NH * DH, 0, nullptr, f->q);
    fb_attn<<<8 * NH, DH, 0, st>>>(f->q, (BP)d_in[1], (BP)d_in[2], f->o);
    fb_gemv<<<dim3(DM / 128, 8), 128, 0, st>>>(f->o, (BP)d_in[4], NH * DH, DM, 2, d_in[0], f->h);
    fb_ln<<<8, 32, 0, st>>>(nullptr, f->h, f->a);
    fb_gemv<<<dim3(FF / 128, 8), 128, 0, st>>>(f->a, (BP)d_in[6], DM, FF, 1, nullptr, f->u);
    fb_gemv<<<dim3(DM / 128, 8), 128, 0, st>>>(f->u, (BP)d_in[7], FF, DM, 3, f->h, d_out);
}

}

extern "C" void kernel_launch(void* const* d_in, const int* in_sizes, int n_in, void* d_out, int out_size) {
    (void)in_sizes; (void)n_in; (void)out_size;
    void* fn = nullptr;
    cudaDriverEntryPointQueryResult qr;
    cudaGetDriverEntryPoint("cuTensorMapEncodeTiled", &fn, cudaEnableDefault, &qr);
    int dev = 0, sms = 0, per_sm = 0;
    cudaGetDevice(&dev);
    cudaDeviceGetAttribute(&sms, cudaDevAttrMultiProcessorCount, dev);
    cudaFuncSetAttribute(fused_decode_kernel, cudaFuncAttributeMaxDynamicSharedMemorySize, SM_TOTAL + 1024);
    cudaOccupancyMaxActiveBlocksPerMultiprocessor(&per_sm, fused_decode_kernel, NTHREADS, SM_TOTAL + 1024);
    if (!fn || sms * per_sm < NCTA) {
        fallback_launch(d_in, d_out, cudaStreamPerThread);
        return;
    }
    EncodeFn enc = (EncodeFn)fn;
    CUtensorMap tk, tv, tq, to, t1, t2;
    const uint64_t kv_lines = 8ull * NH * SK * 3;
    make_map(enc, &tk, d_in[1], 64, kv_lines, 64, 192, 0, CU_TENSOR_MAP_SWIZZLE_128B);
    make_map(enc, &tv, d_in[2], 64, kv_lines, 64, 192, 0, CU_TENSOR_MAP_SWIZZLE_128B);
    make_map(enc, &tq, d_in[3], NH * DH, DM, 64, 160, 0, CU_TENSOR_MAP_SWIZZLE_128B);
    make_map(enc, &to, d_in[4], DM, NH * DH, 64, 192, 0, CU_TENSOR_MAP_SWIZZLE_128B);
    make_map(enc, &t1, d_in[6], FF, DM, 32, 160, 2, CU_TENSOR_MAP_SWIZZLE_64B);
    make_map(enc, &t2, d_in[7], DM, FF, 16, 256, 3, CU_TENSOR_MAP_SWIZZLE_32B);
    fused_decode_kernel<<<NCTA, NTHREADS, SM_TOTAL + 1024, cudaStreamPerThread>>>(
        tk, tv, tq, to, t1, t2, (const __nv_bfloat16*)d_in[0], (__nv_bfloat16*)d_out);
}
```
